```python
import torch

def _softmax(x, axis=-1):
    return torch.softmax(x, dim=axis)
def _gelu(x):
    return torch.nn.functional.gelu(x, approximate="tanh")
def _silu(x):
    return torch.nn.functional.silu(x)
def _sigmoid(x):
    return torch.sigmoid(x)
def _layernorm(x, axis=-1, eps=1e-5):
    m = x.mean(dim=axis, keepdim=True)
    v = x.var(dim=axis, keepdim=True, unbiased=False)
    return (x - m) / torch.sqrt(v + eps)
def _scatter_add(tgt, idx, src, axis=0):
    return tgt.clone().index_add_(axis, idx, src)
def _segment_sum(src, seg, n):
    out = torch.zeros((n,) + src.shape[1:], dtype=src.dtype)
    return out.index_add_(0, seg, src)
def _pad(x, pw):
    flat = tuple(v for pair in reversed(pw) for v in pair)
    return torch.nn.functional.pad(x, flat)

kernel_name = 'parallel_sum__ssm_conv_s4__glu_gated_swiglu__prompt'

def setup_inputs():

    _w = (lambda a: (lambda t: t.to(torch.bfloat16) if t.is_floating_point() else t)(torch.as_tensor(a)))
    def _A_setup():
        B, L, D, N = 1, 2048, 576, 128
        A_re = -(lambda _x: torch.exp(torch.as_tensor(_x)))((lambda *s: torch.randn(*s, dtype=torch.bfloat16) * 6.4)(D, N))
        A_im = torch.pi * (lambda *s: torch.randn(*s, dtype=torch.bfloat16) * 0.05)(D, N)
        B_re = (lambda *s: torch.randn(*s, dtype=torch.bfloat16) * 0.1)(D, N)
        B_im = (lambda *s: torch.randn(*s, dtype=torch.bfloat16) * 0.1)(D, N)
        C_re = (lambda *s: torch.randn(*s, dtype=torch.bfloat16) * 0.1)(D, N)
        C_im = (lambda *s: torch.randn(*s, dtype=torch.bfloat16) * 0.1)(D, N)
        log_dt = (lambda *s: torch.randn(*s, dtype=torch.bfloat16) * 0.05)(D) * 0.5 - 4.0
        Dskip = (lambda *s: torch.randn(*s, dtype=torch.bfloat16) * 0.05)(D)
        return {
            "u": _w((lambda *s: torch.randn(*s, dtype=torch.bfloat16) * 0.05)(B, L, D)),
            "A_re": _w(A_re),
            "A_im": _w(A_im),
            "B_re": _w(B_re),
            "B_im": _w(B_im),
            "C_re": _w(C_re),
            "C_im": _w(C_im),
            "log_dt": _w(log_dt),
            "Dskip": _w(Dskip),
        }
    _A_in = _A_setup()

    def _B_setup():
        B, S, D, F = 1, 2048, 576, 4608
        return {
            "x": _w((lambda *s: torch.randn(*s, dtype=torch.bfloat16) * 0.05)(B, S, D)),
            "w1": _w((lambda *s: torch.randn(*s, dtype=torch.bfloat16) * 0.4)(D, F) * (2.0 / D) ** 0.5),
            "w3": _w((lambda *s: torch.randn(*s, dtype=torch.bfloat16) * 0.4)(D, F) * (2.0 / D) ** 0.5),
            "w2": _w((lambda *s: torch.randn(*s, dtype=torch.bfloat16) * 0.4)(F, D) * (2.0 / F) ** 0.5),
        }
    _B_in = _B_setup()

    return {
        "A_u": _A_in["u"],
        "A_A_re": _A_in["A_re"],
        "A_A_im": _A_in["A_im"],
        "A_B_re": _A_in["B_re"],
        "A_B_im": _A_in["B_im"],
        "A_C_re": _A_in["C_re"],
        "A_C_im": _A_in["C_im"],
        "A_log_dt": _A_in["log_dt"],
        "A_Dskip": _A_in["Dskip"],
        "B_x": _B_in["x"],
        "B_w1": _B_in["w1"],
        "B_w3": _B_in["w3"],
        "B_w2": _B_in["w2"],
    }

def reference(A_u, A_A_re, A_A_im, A_B_re, A_B_im, A_C_re, A_C_im, A_log_dt, A_Dskip, B_x, B_w1, B_w3, B_w2):
    def _A_ref(u, A_re, A_im, B_re, B_im, C_re, C_im, log_dt, Dskip):
        Bsz, L, D = u.shape
        dt = torch.exp(log_dt)[:, None]
        A = A_re + 1j * A_im
        Bc = B_re + 1j * B_im
        Cc = C_re + 1j * C_im
        logdA = dt * A
        dB = dt * Bc
        l = (lambda x, dt: x.to(dt))(torch.arange(L), A_re.dtype)
        P = torch.exp(logdA[:, :, None] * l[None, None, :])
        K = torch.einsum("dn,dnl,dn->dl", Cc, P, dB).real
        L2 = 2 * L
        Kp = _pad(K, ((0, 0), (0, L)))
        up = (lambda x, *d: x.permute(*d))(u, 0, 2, 1)
        up = _pad(up, ((0, 0), (0, 0), (0, L)))
        Kf = (lambda x, axes=(-2,-1): torch.fft.rfft2(x.float(), dim=axes))(Kp[:, None, :], axes=(-2, -1))
        Uf = (lambda x, axes=(-2,-1): torch.fft.rfft2(x.float(), dim=axes))(up[:, :, None, :], axes=(-2, -1))
        Yf = Uf * Kf[None, :, :, :]
        y = (lambda x, s, axes=(-2,-1): torch.fft.irfft2(x, s=s, dim=axes).to(torch.bfloat16))(Yf, (1, L2), axes=(-2, -1))[:, :, 0, :L]
        y = (lambda x, *d: x.permute(*d))(y, 0, 2, 1) + u * Dskip[None, None, :]
        return y

    def _B_ref(x, w1, w3, w2):
        gate = torch.einsum("bsd,df->bsf", x, w1)
        up = torch.einsum("bsd,df->bsf", x, w3)
        h = _silu(gate) * up
        out = torch.einsum("bsf,fd->bsd", h, w2)
        return out

    x = A_u
    xn = _layernorm(x, axis=-1)
    return x + _A_ref(xn, A_A_re, A_A_im, A_B_re, A_B_im, A_C_re, A_C_im, A_log_dt, A_Dskip) + _B_ref(xn, B_w1, B_w3, B_w2)
```

```cpp
#include <cuda_runtime.h>
#include <cuda_bf16.h>
#include <cuda.h>
#include <stdint.h>

namespace {

constexpr int L_ = 2048, D_ = 576, F_ = 4608, NM_ = 128;
constexpr int NST = 7;
#define LAGPOS 3
#define JOBMASK 0x1a8
constexpr int PFD = 24;
constexpr uint32_t STAGE = 16384;
constexpr uint32_t OFF_XS = NST * STAGE;
constexpr uint32_t OFF_HS = OFF_XS + 32768;
constexpr uint32_t OFF_W = OFF_HS + 32768;
constexpr uint32_t QP = 296;
constexpr uint32_t TP = 144;
constexpr uint32_t KDH = 1184;
constexpr uint32_t KDP = 2 * KDH;
constexpr uint32_t W_X = 0;
constexpr uint32_t W_S7 = 5248;
constexpr uint32_t W_S9 = W_S7 + 2176;
constexpr uint32_t W_H = W_S9 + 2176;
constexpr uint32_t W_Q = W_H + 4608;
constexpr uint32_t W_E = W_Q + 8288;
constexpr uint32_t W_T = 0;
constexpr uint32_t W_KC = W_E + 14336 + 1024;
constexpr uint32_t W_KD = W_E + 16384;
constexpr uint32_t W_SIZE = W_KD + 4 * KDP;
constexpr uint32_t W_STRIDE = 49152;
static_assert(W_E % 16 == 0 && W_S7 % 128 == 0 && W_H % 128 == 0 && 4 * 56 * TP <= W_KC, "alias");
constexpr uint32_t OFF_STAT = OFF_W + W_STRIDE;
constexpr uint32_t OFF_BAR = OFF_STAT + 1024;
constexpr uint32_t SMEM_BYTES = OFF_BAR + 512 + 1024;
static_assert(W_SIZE <= W_STRIDE, "workspace");
static_assert(SMEM_BYTES <= 232448, "smem");
constexpr uint32_t B_FULL = 0, B_EMPTY = 8 * NST, B_XFULL = 16 * NST, B_XFREE = B_XFULL + 72, B_STATS = B_XFREE + 8,
                   B_PRESUM = B_STATS + 8, B_LAG = B_PRESUM + 8, B_XCH = B_LAG + 8, B_CREADY = B_XCH + 32,
                   B_CDONE = B_CREADY + 32, B_PART = B_CDONE + 32, B_XROW = B_PART + 64, B_FET = B_XROW + 8, B_FREE = B_FET + 40, B_RST = B_FREE + 32, B_EPOCH = B_RST + 8;
constexpr int KR_T = 559;

__device__ uint4 g_hpark[128 * 6 * 4 * 256];
__device__ uint4 g_part[16 * 9 * 8 * 2 * 4 * 128];
__device__ uint4 g_xt[D_ * 256];
__device__ uint4 g_y[32 * 144 * 32];
struct alignas(32) Flag {
  uint4 v[2];
};
__device__ Flag g_fx[128];
__device__ Flag g_fy[144];
__device__ Flag g_fp[16 * 8 * 2 * 4];
__device__ unsigned g_epoch;

__device__ __forceinline__ uint32_t smem_u32(const void* p) { return (uint32_t)__cvta_generic_to_shared(p); }
__device__ __forceinline__ void mbar_init(uint32_t bar, uint32_t cnt) {
  asm volatile("mbarrier.init.shared::cta.b64 [%0], %1;" ::"r"(bar), "r"(cnt) : "memory");
}
__device__ __forceinline__ void mbar_expect_tx(uint32_t bar, uint32_t bytes) {
  asm volatile("mbarrier.arrive.expect_tx.shared::cta.b64 _, [%0], %1;" ::"r"(bar), "r"(bytes) : "memory");
}
__device__ __forceinline__ void mbar_arrive(uint32_t bar) {
  asm volatile("mbarrier.arrive.shared::cta.b64 _, [%0];" ::"r"(bar) : "memory");
}
__device__ __forceinline__ void mbar_arrive_cl(uint32_t cbar) {
  asm volatile("mbarrier.arrive.shared::cluster.b64 _, [%0];" ::"r"(cbar) : "memory");
}
__device__ __forceinline__ uint32_t mapa(uint32_t a, uint32_t cta) {
  uint32_t r;
  asm volatile("mapa.shared::cluster.u32 %0, %1, %2;" : "=r"(r) : "r"(a), "r"(cta));
  return r;
}
#define TO_NOTE
#define TO_ARG(site)
template <int SITE>
__device__ __forceinline__ void mbar_wait_(uint32_t bar, uint32_t parity) {
  asm volatile(
      "{\n.reg .pred p;\n.reg .u32 c, v;\nmov.u32 c, 0;\n"
      "LW:\nmbarrier.try_wait.parity.shared::cta.b64 p, [%0], %1;\n@p bra LD;\n"
      "add.u32 c, c, 1;\nsetp.lt.u32 p, c, 4000;\n@p bra LW;\n" TO_NOTE "LD:\n}" ::"r"(bar),
      "r"(parity) TO_ARG(SITE)
      : "memory");
}
template <int SITE>
__device__ __forceinline__ void flag_wait_(const Flag* f, unsigned ep) {
  asm volatile(
      "{\n.reg .pred p;\n.reg .u32 c, v;\nmov.u32 c, 0;\n"
      "LW:\nld.relaxed.gpu.global.u32 v, [%0];\nsetp.eq.u32 p, v, %1;\n@p bra LD;\n"
      "nanosleep.u32 100;\nadd.u32 c, c, 1;\nsetp.lt.u32 p, c, 8000;\n@p bra LW;\n" TO_NOTE "LD:\n}" ::"l"(f),
      "r"(ep) TO_ARG(SITE)
      : "memory");
}
__device__ __forceinline__ void fence_async_global() { asm volatile("fence.proxy.async.global;" ::: "memory"); }
#define mbar_wait mbar_wait_<__COUNTER__>
#define flag_wait flag_wait_<__COUNTER__>
__device__ __forceinline__ void flag_set(Flag* f, unsigned ep, int lane) {
  asm volatile("fence.acq_rel.gpu;\nst.relaxed.gpu.global.v4.u32 [%0], {%1,%1,%1,%1};" ::"l"(&f->v[lane]), "r"(ep) : "memory");
}
__device__ __forceinline__ void bar_sync(int id, int n) { asm volatile("bar.sync %0, %1;" ::"r"(id), "r"(n) : "memory"); }
__device__ __forceinline__ void fence_async_smem() { asm volatile("fence.proxy.async.shared::cta;" ::: "memory"); }
__device__ __forceinline__ void tma2d(uint32_t dst, const CUtensorMap* m, int c0, int c1, uint32_t bar) {
  asm volatile("cp.async.bulk.tensor.2d.shared::cluster.global.mbarrier::complete_tx::bytes [%0], [%1, {%3, %4}], [%2];" ::"r"(dst),
               "l"(m), "r"(bar), "r"(c0), "r"(c1)
               : "memory");
}
__device__ __forceinline__ void tma2d_mc(uint32_t dst, const CUtensorMap* m, int c0, int c1, uint32_t bar) {
  asm volatile(
      "cp.async.bulk.tensor.2d.shared::cluster.global.mbarrier::complete_tx::bytes.multicast::cluster [%0], [%1, {%3, %4}], [%2], %5;" ::"r"(dst),
      "l"(m), "r"(bar), "r"(c0), "r"(c1), "h"((uint16_t)3)
      : "memory");
}
__device__ __forceinline__ void tma2d_prefetch(const CUtensorMap* m, int c0, int c1) {
  asm volatile("cp.async.bulk.prefetch.tensor.2d.L2.global.tile [%0, {%1, %2}];" ::"l"(m), "r"(c0), "r"(c1) : "memory");
}
__device__ __forceinline__ void bulk_g2s(uint32_t dst, const void* src, uint32_t bytes, uint32_t bar) {
  asm volatile("cp.async.bulk.shared::cluster.global.mbarrier::complete_tx::bytes [%0], [%1], %2, [%3];" ::"r"(dst), "l"(src),
               "r"(bytes), "r"(bar)
               : "memory");
}
__device__ __forceinline__ void wg_fence() { asm volatile("wgmma.fence.sync.aligned;" ::: "memory"); }
__device__ __forceinline__ void wg_commit() { asm volatile("wgmma.commit_group.sync.aligned;" ::: "memory"); }
template <int N>
__device__ __forceinline__ void wg_wait() { asm volatile("wgmma.wait_group.sync.aligned %0;" ::"n"(N) : "memory"); }
template <int N>
__device__ __forceinline__ void pin(float (&d)[N]) {
#pragma unroll
  for (int i = 0; i < N; i++) asm volatile("" : "+f"(d[i])::"memory");
}
__device__ __forceinline__ uint64_t make_desc(uint32_t addr, uint32_t lbo, uint32_t sbo, uint32_t swz) {
  return (uint64_t)((addr & 0x3FFFF) >> 4) | ((uint64_t)(lbo >> 4) << 16) | ((uint64_t)(sbo >> 4) << 32) | ((uint64_t)swz << 62);
}
__device__ __forceinline__ uint32_t pack2(float lo, float hi) {
  uint32_t r;
  asm("cvt.rn.bf16x2.f32 %0, %1, %2;" : "=r"(r) : "f"(hi), "f"(lo));
  return r;
}
__device__ __forceinline__ float bf_lo(uint32_t v) { return __uint_as_float(v << 16); }
__device__ __forceinline__ float bf_hi(uint32_t v) { return __uint_as_float(v & 0xffff0000u); }
__device__ __forceinline__ float bf_round(float v) { return bf_lo(pack2(v, 0.f)); }
__device__ __forceinline__ uint32_t hsub2(uint32_t a, uint32_t b) {
  uint32_t r;
  asm("sub.rn.bf16x2 %0, %1, %2;" : "=r"(r) : "r"(a), "r"(b));
  return r;
}
__device__ __forceinline__ uint32_t hadd2(uint32_t a, uint32_t b) {
  uint32_t r;
  asm("add.rn.bf16x2 %0, %1, %2;" : "=r"(r) : "r"(a), "r"(b));
  return r;
}
__device__ __forceinline__ uint32_t hnorm2(uint32_t d, uint32_t rhi, uint32_t rlo) {
  uint32_t r;
  asm("{\n.reg .b32 t;\nmul.rn.bf16x2 t, %1, %3;\nfma.rn.bf16x2 %0, %1, %2, t;\n}" : "=r"(r) : "r"(d), "r"(rhi), "r"(rlo));
  return r;
}
__device__ __forceinline__ float tanh_ap(float x) {
  float y;
  asm("tanh.approx.f32 %0, %1;" : "=f"(y) : "f"(x));
  return y;
}
__device__ __forceinline__ float ex2_ap(float x) {
  float y;
  asm("ex2.approx.ftz.f32 %0, %1;" : "=f"(y) : "f"(x));
  return y;
}
__device__ __forceinline__ void ldsm4(uint32_t& r0, uint32_t& r1, uint32_t& r2, uint32_t& r3, uint32_t a) {
  asm volatile("ldmatrix.sync.aligned.m8n8.x4.shared.b16 {%0,%1,%2,%3}, [%4];" : "=r"(r0), "=r"(r1), "=r"(r2), "=r"(r3) : "r"(a) : "memory");
}
__device__ __forceinline__ void ldsm2(uint32_t& r0, uint32_t& r1, uint32_t a) {
  asm volatile("ldmatrix.sync.aligned.m8n8.x2.shared.b16 {%0,%1}, [%2];" : "=r"(r0), "=r"(r1) : "r"(a) : "memory");
}
__device__ __forceinline__ void stsm4(uint32_t a, uint32_t r0, uint32_t r1, uint32_t r2, uint32_t r3) {
  asm volatile("stmatrix.sync.aligned.m8n8.x4.shared.b16 [%0], {%1,%2,%3,%4};" ::"r"(a), "r"(r0), "r"(r1), "r"(r2), "r"(r3) : "memory");
}
__device__ __forceinline__ void hmma(float (&c)[4], uint32_t a0, uint32_t a1, uint32_t a2, uint32_t a3, uint32_t b0, uint32_t b1) {
  asm volatile("mma.sync.aligned.m16n8k16.row.col.f32.bf16.bf16.f32 {%0,%1,%2,%3}, {%4,%5,%6,%7}, {%8,%9}, {%0,%1,%2,%3};"
               : "+f"(c[0]), "+f"(c[1]), "+f"(c[2]), "+f"(c[3])
               : "r"(a0), "r"(a1), "r"(a2), "r"(a3), "r"(b0), "r"(b1));
}
__device__ __forceinline__ uint32_t opaque(uint32_t a) { asm volatile("" : "+r"(a)::"memory"); return a; }
__device__ __forceinline__ uint32_t lds32_f(uint32_t a) {
  uint32_t r;
  asm("ld.shared.b32 %0, [%1];" : "=r"(r) : "r"(a));
  return r;
}
__device__ __forceinline__ uint32_t lds16_f(uint32_t a) {
  uint16_t r;
  asm("ld.shared.u16 %0, [%1];" : "=h"(r) : "r"(a));
  return r;
}
__device__ __forceinline__ void lds64(uint32_t& r0, uint32_t& r1, uint32_t a) {
  asm volatile("ld.shared.v2.b32 {%0,%1}, [%2];" : "=r"(r0), "=r"(r1) : "r"(a) : "memory");
}
__device__ __forceinline__ void sts64(uint32_t a, uint32_t r0, uint32_t r1) {
  asm volatile("st.shared.v2.b32 [%0], {%1,%2};" ::"r"(a), "r"(r0), "r"(r1) : "memory");
}
__device__ __forceinline__ uint32_t vmov(uint32_t a) {
  uint32_t r;
  asm volatile("mov.b32 %0, %1;" : "=r"(r) : "r"(a));
  return r;
}
__device__ __forceinline__ float sqrt_ap(float x) {
  float y;
  asm("sqrt.approx.f32 %0, %1;" : "=f"(y) : "f"(x));
  return y;
}
__device__ __forceinline__ float rcp_ap(float x) {
  float y;
  asm("rcp.approx.f32 %0, %1;" : "=f"(y) : "f"(x));
  return y;
}
__device__ __forceinline__ uint32_t tid_now() {
  uint32_t r;
  asm volatile("mov.u32 %0, %%tid.x;" : "=r"(r));
  return r;
}
__device__ __forceinline__ uint32_t frag_off(uint32_t t) {
  return ((t & 0xe0u) >> 1 | (t & 15u)) * 128 + ((((t >> 4) & 1u) ^ (t & 7u)) << 4);
}
__device__ __forceinline__ uint32_t stat_off(uint32_t t) { return ((t & 0xe0u) >> 1 | (t & 31u) >> 2) * 8; }
__device__ __forceinline__ uint32_t swz(uint32_t a) { return a ^ (((a >> 7) & 3) << 4); }
__device__ __forceinline__ void ldsm4t(uint32_t& r0, uint32_t& r1, uint32_t& r2, uint32_t& r3, uint32_t a) {
  asm volatile("ldmatrix.sync.aligned.m8n8.x4.trans.shared.b16 {%0,%1,%2,%3}, [%4];" : "=r"(r0), "=r"(r1), "=r"(r2), "=r"(r3) : "r"(a) : "memory");
}
__device__ __forceinline__ void lds128(uint32_t& r0, uint32_t& r1, uint32_t& r2, uint32_t& r3, uint32_t a) {
  asm volatile("ld.shared.v4.b32 {%0,%1,%2,%3}, [%4];" : "=r"(r0), "=r"(r1), "=r"(r2), "=r"(r3) : "r"(a) : "memory");
}
__device__ __forceinline__ void sts128(uint32_t a, uint32_t r0, uint32_t r1, uint32_t r2, uint32_t r3) {
  asm volatile("st.shared.v4.b32 [%0], {%1,%2,%3,%4};" ::"r"(a), "r"(r0), "r"(r1), "r"(r2), "r"(r3) : "memory");
}
__device__ __forceinline__ uint32_t lds32(uint32_t a) {
  uint32_t r;
  asm volatile("ld.shared.b32 %0, [%1];" : "=r"(r) : "r"(a) : "memory");
  return r;
}
__device__ __forceinline__ void sts32(uint32_t a, uint32_t v) { asm volatile("st.shared.b32 [%0], %1;" ::"r"(a), "r"(v) : "memory"); }
__device__ __forceinline__ void sts16(uint32_t a, uint32_t v) { asm volatile("st.shared.u16 [%0], %1;" ::"r"(a), "h"((uint16_t)v) : "memory"); }
__device__ __forceinline__ uint4 ldg128_cg(const uint4* p) {
  uint4 v;
  asm volatile("ld.relaxed.gpu.global.v4.u32 {%0,%1,%2,%3}, [%4];" : "=r"(v.x), "=r"(v.y), "=r"(v.z), "=r"(v.w) : "l"(p) : "memory");
  return v;
}
__device__ __forceinline__ void stg128(void* p, uint32_t a, uint32_t b, uint32_t c, uint32_t d) {
  asm volatile("st.global.v4.u32 [%0], {%1,%2,%3,%4};" ::"l"(p), "r"(a), "r"(b), "r"(c), "r"(d) : "memory");
}
__device__ __forceinline__ void stg128_rlx(void* p, uint32_t a, uint32_t b, uint32_t c, uint32_t d) {
  asm volatile("st.relaxed.gpu.global.v4.u32 [%0], {%1,%2,%3,%4};" ::"l"(p), "r"(a), "r"(b), "r"(c), "r"(d) : "memory");
}
constexpr uint32_t EMPTY = 0xffffffffu;
__device__ __forceinline__ uint32_t ldg32_cg(const void* p) {
  uint32_t v;
  asm volatile("ld.relaxed.gpu.global.u32 %0, [%1];" : "=r"(v) : "l"(p) : "memory");
  return v;
}

#define TR(slot)
#define TRX(slot)

__device__ __forceinline__ void mma_n128_rs(float (&d)[64], uint32_t a0, uint32_t a1, uint32_t a2, uint32_t a3, uint64_t db, int sd) {
  asm volatile("{\n.reg .pred p;\nsetp.ne.b32 p, %69, 0;\n"
    "wgmma.mma_async.sync.aligned.m64n128k16.f32.bf16.bf16 {%0, %1, %2, %3, %4, %5, %6, %7, %8, %9, %10, %11, %12, %13, %14, %15, %16, %17, %18, %19, %20, %21, %22, %23, %24, %25, %26, %27, %28, %29, %30, %31, %32, %33, %34, %35, %36, %37, %38, %39, %40, %41, %42, %43, %44, %45, %46, %47, %48, %49, %50, %51, %52, %53, %54, %55, %56, %57, %58, %59, %60, %61, %62, %63}, {%64,%65,%66,%67}, %68, p, 1, 1, 1;\n}"
    : "+f"(d[0]), "+f"(d[1]), "+f"(d[2]), "+f"(d[3]), "+f"(d[4]), "+f"(d[5]), "+f"(d[6]), "+f"(d[7]), "+f"(d[8]), "+f"(d[9]), "+f"(d[10]), "+f"(d[11]), "+f"(d[12]), "+f"(d[13]), "+f"(d[14]), "+f"(d[15]), "+f"(d[16]), "+f"(d[17]), "+f"(d[18]), "+f"(d[19]), "+f"(d[20]), "+f"(d[21]), "+f"(d[22]), "+f"(d[23]), "+f"(d[24]), "+f"(d[25]), "+f"(d[26]), "+f"(d[27]), "+f"(d[28]), "+f"(d[29]), "+f"(d[30]), "+f"(d[31]), "+f"(d[32]), "+f"(d[33]), "+f"(d[34]), "+f"(d[35]), "+f"(d[36]), "+f"(d[37]), "+f"(d[38]), "+f"(d[39]), "+f"(d[40]), "+f"(d[41]), "+f"(d[42]), "+f"(d[43]), "+f"(d[44]), "+f"(d[45]), "+f"(d[46]), "+f"(d[47]), "+f"(d[48]), "+f"(d[49]), "+f"(d[50]), "+f"(d[51]), "+f"(d[52]), "+f"(d[53]), "+f"(d[54]), "+f"(d[55]), "+f"(d[56]), "+f"(d[57]), "+f"(d[58]), "+f"(d[59]), "+f"(d[60]), "+f"(d[61]), "+f"(d[62]), "+f"(d[63])
    : "r"(a0), "r"(a1), "r"(a2), "r"(a3), "l"(db), "r"(sd));
}
__device__ __forceinline__ void mma_n128_ss(float (&d)[64], uint64_t da, uint64_t db, int sd) {
  asm volatile("{\n.reg .pred p;\nsetp.ne.b32 p, %66, 0;\n"
    "wgmma.mma_async.sync.aligned.m64n128k16.f32.bf16.bf16 {%0, %1, %2, %3, %4, %5, %6, %7, %8, %9, %10, %11, %12, %13, %14, %15, %16, %17, %18, %19, %20, %21, %22, %23, %24, %25, %26, %27, %28, %29, %30, %31, %32, %33, %34, %35, %36, %37, %38, %39, %40, %41, %42, %43, %44, %45, %46, %47, %48, %49, %50, %51, %52, %53, %54, %55, %56, %57, %58, %59, %60, %61, %62, %63}, %64, %65, p, 1, 1, 0, 1;\n}"
    : "+f"(d[0]), "+f"(d[1]), "+f"(d[2]), "+f"(d[3]), "+f"(d[4]), "+f"(d[5]), "+f"(d[6]), "+f"(d[7]), "+f"(d[8]), "+f"(d[9]), "+f"(d[10]), "+f"(d[11]), "+f"(d[12]), "+f"(d[13]), "+f"(d[14]), "+f"(d[15]), "+f"(d[16]), "+f"(d[17]), "+f"(d[18]), "+f"(d[19]), "+f"(d[20]), "+f"(d[21]), "+f"(d[22]), "+f"(d[23]), "+f"(d[24]), "+f"(d[25]), "+f"(d[26]), "+f"(d[27]), "+f"(d[28]), "+f"(d[29]), "+f"(d[30]), "+f"(d[31]), "+f"(d[32]), "+f"(d[33]), "+f"(d[34]), "+f"(d[35]), "+f"(d[36]), "+f"(d[37]), "+f"(d[38]), "+f"(d[39]), "+f"(d[40]), "+f"(d[41]), "+f"(d[42]), "+f"(d[43]), "+f"(d[44]), "+f"(d[45]), "+f"(d[46]), "+f"(d[47]), "+f"(d[48]), "+f"(d[49]), "+f"(d[50]), "+f"(d[51]), "+f"(d[52]), "+f"(d[53]), "+f"(d[54]), "+f"(d[55]), "+f"(d[56]), "+f"(d[57]), "+f"(d[58]), "+f"(d[59]), "+f"(d[60]), "+f"(d[61]), "+f"(d[62]), "+f"(d[63])
    : "l"(da), "l"(db), "r"(sd));
}
__device__ __forceinline__ void mma_n64_rs(float (&d)[32], uint32_t a0, uint32_t a1, uint32_t a2, uint32_t a3, uint64_t db, int sd) {
  asm volatile("{\n.reg .pred p;\nsetp.ne.b32 p, %37, 0;\n"
    "wgmma.mma_async.sync.aligned.m64n64k16.f32.bf16.bf16 {%0, %1, %2, %3, %4, %5, %6, %7, %8, %9, %10, %11, %12, %13, %14, %15, %16, %17, %18, %19, %20, %21, %22, %23, %24, %25, %26, %27, %28, %29, %30, %31}, {%32,%33,%34,%35}, %36, p, 1, 1, 1;\n}"
    : "+f"(d[0]), "+f"(d[1]), "+f"(d[2]), "+f"(d[3]), "+f"(d[4]), "+f"(d[5]), "+f"(d[6]), "+f"(d[7]), "+f"(d[8]), "+f"(d[9]), "+f"(d[10]), "+f"(d[11]), "+f"(d[12]), "+f"(d[13]), "+f"(d[14]), "+f"(d[15]), "+f"(d[16]), "+f"(d[17]), "+f"(d[18]), "+f"(d[19]), "+f"(d[20]), "+f"(d[21]), "+f"(d[22]), "+f"(d[23]), "+f"(d[24]), "+f"(d[25]), "+f"(d[26]), "+f"(d[27]), "+f"(d[28]), "+f"(d[29]), "+f"(d[30]), "+f"(d[31])
    : "r"(a0), "r"(a1), "r"(a2), "r"(a3), "l"(db), "r"(sd));
}
__device__ __forceinline__ void mma_n64_ss(float (&d)[32], uint64_t da, uint64_t db, int sd) {
  asm volatile("{\n.reg .pred p;\nsetp.ne.b32 p, %34, 0;\n"
    "wgmma.mma_async.sync.aligned.m64n64k16.f32.bf16.bf16 {%0, %1, %2, %3, %4, %5, %6, %7, %8, %9, %10, %11, %12, %13, %14, %15, %16, %17, %18, %19, %20, %21, %22, %23, %24, %25, %26, %27, %28, %29, %30, %31}, %32, %33, p, 1, 1, 0, 1;\n}"
    : "+f"(d[0]), "+f"(d[1]), "+f"(d[2]), "+f"(d[3]), "+f"(d[4]), "+f"(d[5]), "+f"(d[6]), "+f"(d[7]), "+f"(d[8]), "+f"(d[9]), "+f"(d[10]), "+f"(d[11]), "+f"(d[12]), "+f"(d[13]), "+f"(d[14]), "+f"(d[15]), "+f"(d[16]), "+f"(d[17]), "+f"(d[18]), "+f"(d[19]), "+f"(d[20]), "+f"(d[21]), "+f"(d[22]), "+f"(d[23]), "+f"(d[24]), "+f"(d[25]), "+f"(d[26]), "+f"(d[27]), "+f"(d[28]), "+f"(d[29]), "+f"(d[30]), "+f"(d[31])
    : "l"(da), "l"(db), "r"(sd));
}
__device__ __forceinline__ void cmma_n64(float (&d)[32], uint32_t a0, uint32_t a1, uint32_t a2, uint32_t a3, uint64_t db, int sd) {
  asm volatile("{\n.reg .pred p;\nsetp.ne.b32 p, %37, 0;\n"
    "wgmma.mma_async.sync.aligned.m64n64k16.f32.bf16.bf16 {%0, %1, %2, %3, %4, %5, %6, %7, %8, %9, %10, %11, %12, %13, %14, %15, %16, %17, %18, %19, %20, %21, %22, %23, %24, %25, %26, %27, %28, %29, %30, %31}, {%32,%33,%34,%35}, %36, p, 1, 1, 0;\n}"
    : "+f"(d[0]), "+f"(d[1]), "+f"(d[2]), "+f"(d[3]), "+f"(d[4]), "+f"(d[5]), "+f"(d[6]), "+f"(d[7]), "+f"(d[8]), "+f"(d[9]), "+f"(d[10]), "+f"(d[11]), "+f"(d[12]), "+f"(d[13]), "+f"(d[14]), "+f"(d[15]), "+f"(d[16]), "+f"(d[17]), "+f"(d[18]), "+f"(d[19]), "+f"(d[20]), "+f"(d[21]), "+f"(d[22]), "+f"(d[23]), "+f"(d[24]), "+f"(d[25]), "+f"(d[26]), "+f"(d[27]), "+f"(d[28]), "+f"(d[29]), "+f"(d[30]), "+f"(d[31])
    : "r"(a0), "r"(a1), "r"(a2), "r"(a3), "l"(db), "r"(sd));
}

struct Params {
  const __nv_bfloat16 *x, *a_re, *a_im, *b_re, *b_im, *c_re, *c_im, *log_dt, *dskip;
  __nv_bfloat16* out;
};

template <bool B>
struct BoolC {
  static constexpr bool value = B;
};
struct KParams {
  uint2 are, aim, bre, bim, cre, cim;
  __nv_bfloat16 ldt;
};

struct cf {
  float r, i;
};
__device__ __forceinline__ cf cmul(cf a, cf b) { return {fmaf(a.r, b.r, -(a.i * b.i)), fmaf(a.r, b.i, a.i * b.r)}; }
__device__ __forceinline__ cf cmulc(cf a, cf b) { return {fmaf(a.r, b.r, a.i * b.i), fmaf(a.i, b.r, -(a.r * b.i))}; }
__device__ __forceinline__ cf csq(cf a) { return {fmaf(a.r, a.r, -(a.i * a.i)), (a.r + a.r) * a.i}; }
__device__ __forceinline__ uint32_t cpack(cf a) { return pack2(a.r, a.i); }
__device__ __forceinline__ cf cexp(float a2, float th, float v) {
  const float mag = ex2_ap(a2 * v), ang = th * v;
  return {mag * __cosf(ang), mag * __sinf(ang)};
}

template <int G, int NB>
__device__ __forceinline__ void conv_mma(uint32_t ws, int warp, int lane) {
  ws = __shfl_sync(0xffffffffu, opaque(ws), 0);
  const int g = lane >> 2, c = lane & 3;
  float y[32];
  uint32_t f[NB][4 * G];
  uint32_t prev = 0;
  const uint32_t fa = ws + W_Q + ((warp >> 1) * 14 + g - 2 * c + 6) * QP + (warp & 1) * 8;
  const uint32_t sa = (uint32_t)(4 * ((lane & 7) + 8 * (lane >> 4) + 16 * (warp >> 1)) + 2 * (warp & 1) + ((lane >> 3) & 1) + 4) * 16;
  const uint64_t dx = make_desc(ws + W_X, 16, 512, 2);
  const uint64_t dh = make_desc(ws + W_H, 128, 128, 0);
  constexpr int NS = 39, NG = (NS + G - 1) / G;
  auto load = [&](int gi) {
#pragma unroll
    for (int i = 0; i < G; i++) {
      const int s = gi * G + i;
      if (s >= NS) break;
      uint32_t* r = &f[gi % NB][4 * i];
      if (s < 35) lds64(r[0], r[1], fa + s * 8);
      else ldsm4t(r[0], r[1], r[2], r[3], swz(ws + ((s & 1) ? W_S7 : W_S9) + sa - (s - 34) * 16));
    }
  };
  auto fill = [&](int gi) {
#pragma unroll
    for (int i = 0; i < G; i++) {
      if (gi * G + i >= 35) break;
      uint32_t* r = &f[gi % NB][4 * i];
      r[2] = vmov(prev);
      r[3] = vmov(r[0]);
      prev = (i == G - 1) ? vmov(r[1]) : r[1];
    }
  };
  TR(56);
  load(0);
  if (NB == 3) load(1);
#pragma unroll
  for (int gi = 0; gi < NG; gi++) {
    fill(gi);
    wg_fence();
#pragma unroll
    for (int i = 0; i < G; i++) {
      const int s = gi * G + i;
      if (s >= NS) break;
      const uint32_t* r = &f[gi % NB][4 * i];
      cmma_n64(y, r[0], r[1], r[2], r[3], s < 35 ? dx + (uint64_t)((s >> 1) * 4 + (1 - (s & 1)) * 2) : dh + (uint64_t)((s - 35) * 72), s != 0);
    }
    wg_commit();
    if (NB == 1) {
      wg_wait<0>();
      if (gi + 1 < NG) load(gi + 1);
    } else if (gi + NB - 1 < NG) {
      if (gi > 0) wg_wait<1>();
      load(gi + NB - 1);
    }
  }
  wg_wait<0>();
  pin(y);
  TR(59);
  const uint32_t ea = ws + W_E + (warp * 32 + lane) * 16;
#pragma unroll
  for (int j = 0; j < 8; j++)
    if (j >= 2 || warp < 2) sts128(ea + (7 - j) * 2048, __float_as_uint(y[4 * j]), __float_as_uint(y[4 * j + 1]), __float_as_uint(y[4 * j + 2]), __float_as_uint(y[4 * j + 3]));
  TR(60);
}

__device__ __forceinline__ void conv_out(uint32_t ws, int warp, int lane, uint32_t* yk) {
  const uint32_t ea = ws + W_E + ((warp & 1) * 32 + lane) * 16 + 14336 - (warp >> 1) * 8192;
  uint32_t lo[16], up[16];
#pragma unroll
  for (int j = 0; j < 4; j++) {
    lds128(lo[4 * j], lo[4 * j + 1], lo[4 * j + 2], lo[4 * j + 3], ea - j * 2048);
    up[4 * j] = up[4 * j + 1] = up[4 * j + 2] = up[4 * j + 3] = 0;
    if (j < 2 || warp < 2) lds128(up[4 * j], up[4 * j + 1], up[4 * j + 2], up[4 * j + 3], ea - (j + 2) * 2048 + 1024);
  }
#pragma unroll
  for (int i = 0; i < 8; i++)
    yk[i] = pack2(__uint_as_float(lo[2 * i]) + __uint_as_float(up[2 * i]), __uint_as_float(lo[2 * i + 1]) + __uint_as_float(up[2 * i + 1]));
}
__device__ __forceinline__ void conv_store(const uint32_t (&yk)[4][8], int warp, int lane, int grp) {
  uint2* dst = reinterpret_cast<uint2*>(g_y) + ((size_t)(31 - 16 * (warp >> 1) - (lane & 3)) * 144 + grp) * 64 + (warp & 1) * 16 + (lane >> 2);
#pragma unroll
  for (int i = 0; i < 8; i++) {
    dst[-(4 * (i >> 1)) * 144 * 64 + 32 + (i & 1) * 8] = make_uint2(__byte_perm(yk[0][i], yk[1][i], 0x5410), __byte_perm(yk[2][i], yk[3][i], 0x5410));
    dst[-(4 * (i >> 1)) * 144 * 64 + (i & 1) * 8] = make_uint2(__byte_perm(yk[0][i], yk[1][i], 0x7632), __byte_perm(yk[2][i], yk[3][i], 0x7632));
  }
}

struct Quad {
  uint32_t a, b, c, d;
};
__device__ __forceinline__ Quad cquad(cf v0, cf v1, cf v2, cf v3) { return {cpack(v0), cpack(v1), cpack(v2), cpack(v3)}; }
__device__ __forceinline__ void stq(uint32_t a, const Quad& q) { stsm4(a, q.a, q.b, q.c, q.d); }

__device__ __forceinline__ void kgen(const KParams& kp, const __nv_bfloat16* dskip, uint32_t ws, int warp, int lane) {
  const int g = lane >> 2, c = lane & 3;
  const uint32_t tb = ws + W_T + warp * (56 * TP);
  const uint32_t sa = tb + (lane >> 3) * TP + (lane & 7) * 16;
  const uint32_t la = tb + ((lane & 7) + 8 * ((lane >> 3) & 1)) * TP + (lane >> 4) * 16;
  const uint32_t lb = tb + (16 + (lane & 7) + 8 * (lane >> 4)) * TP + ((lane >> 3) & 1) * 16;
  const float dt = bf_round(expf(__bfloat162float(kp.ldt)));
  float k0 = 0.f;
  float acc[5][4];
#pragma unroll
  for (int t = 0; t < 5; t++)
#pragma unroll
    for (int i = 0; i < 4; i++) acc[t][i] = 0.f;
  uint32_t p0 = kp.are.x, p1 = kp.aim.x, p2 = kp.bre.x, p3 = kp.bim.x, p4 = kp.cre.x, p5 = kp.cim.x;
  cf cb, w1, w8, w128;
  auto anchors = [&]() {
    const float a2 = (dt * bf_lo(p0)) * 1.4426950408889634f, th = dt * bf_lo(p1);
    cb = cmul({bf_lo(p4), bf_lo(p5)}, {dt * bf_lo(p2), dt * bf_lo(p3)});
    cb.i = -cb.i;
    w1 = cexp(a2, th, 1.f); w8 = cexp(a2, th, 8.f); w128 = cexp(a2, th, 128.f);
  };
  TR(44);
  anchors();
#pragma unroll 1
  for (int b = 0; b < 4; b++) {
    k0 += cb.r;
    Quad qa, qb;
    {
      const cf w16 = csq(w8), w32 = csq(w16), w64 = csq(w32);
      const cf v1 = cmulc(cb, w8), v2 = cmulc(cb, w16), v3 = cmulc(v1, w16);
      qa = cquad(cb, v1, v2, v3);
      qb = cquad(cmulc(cb, w64), cmulc(v1, w64), cmulc(v2, w64), cmulc(v3, w64));
      stq(sa, qa);
      const cf v4 = cmulc(cb, w32), v5 = cmulc(v1, w32), v6 = cmulc(v2, w32), v7 = cmulc(v3, w32);
      qa = cquad(v4, v5, v6, v7);
      stq(sa + 8 * TP, qb);
      qb = cquad(cmulc(v4, w64), cmulc(v5, w64), cmulc(v6, w64), cmulc(v7, w64));
      stq(sa + 4 * TP, qa);
    }
    const cf w2 = csq(w1), w4 = csq(w2), w129 = cmul(w1, w128);
    {
      const cf w3 = cmul(w2, w1);
      qa = cquad(w1, w2, w3, w4);
      stq(sa + 12 * TP, qb);
      qb = cquad(w129, cmul(w2, w128), cmul(w3, w128), cmul(w4, w128));
      stq(sa + 16 * TP, qa);
      const cf w5 = cmul(w4, w1), w6 = cmul(w4, w2), w7 = cmul(w4, w3);
      qa = cquad(w5, w6, w7, w8);
      stq(sa + 24 * TP, qb);
      qb = cquad(cmul(w5, w128), cmul(w6, w128), cmul(w7, w128), cmul(w8, w128));
      stq(sa + 20 * TP, qa);
    }
    const cf w258 = csq(w129), w256 = csq(w128), w516 = csq(w258);
    {
      const cf v1 = cmul(w258, w2), v2 = cmul(w258, w4), v3 = cmul(v1, w4);
      qa = cquad(w258, v1, v2, v3);
      stq(sa + 28 * TP, qb);
      qb = cquad(cmul(w258, w128), cmul(v1, w128), cmul(v2, w128), cmul(v3, w128));
      stq(sa + 32 * TP, qa);
    }
    {
      const cf v1 = cmul(w516, w4), v2 = cmul(w516, w128), v3 = cmul(v1, w128);
      qa = cquad(w516, v1, v2, v3);
      stq(sa + 36 * TP, qb);
      qb = cquad(cmul(w516, w256), cmul(v1, w256), cmul(v2, w256), cmul(v3, w256));
      stq(sa + 40 * TP, qa);
    }
    {
      const cf v0 = csq(w516), w512 = csq(w256);
      const cf v1 = cmul(v0, w128), v2 = cmul(v0, w256), v3 = cmul(v1, w256);
      qa = cquad(v0, v1, v2, v3);
      stq(sa + 44 * TP, qb);
      qb = cquad(cmul(v0, w512), cmul(v1, w512), cmul(v2, w512), cmul(v3, w512));
      stq(sa + 48 * TP, qa);
      stq(sa + 52 * TP, qb);
    }
    __syncwarp();
    if (b == 1) { p0 = kp.are.y; p1 = kp.aim.y; p2 = kp.bre.y; p3 = kp.bim.y; p4 = kp.cre.y; p5 = kp.cim.y; }
    else { p0 >>= 16; p1 >>= 16; p2 >>= 16; p3 >>= 16; p4 >>= 16; p5 >>= 16; }
#pragma unroll
    for (int k2 = 0; k2 < 2; k2++) {
      uint32_t fa[2][4], fb[2][10];
#pragma unroll
      for (int k = 0; k < 2; k++) {
        const int ks = 2 * k2 + k;
        ldsm4(fa[k][0], fa[k][1], fa[k][2], fa[k][3], la + ks * 32);
        ldsm4(fb[k][0], fb[k][1], fb[k][2], fb[k][3], lb + ks * 32);
        ldsm4(fb[k][4], fb[k][5], fb[k][6], fb[k][7], lb + 16 * TP + ks * 32);
        ldsm2(fb[k][8], fb[k][9], lb + 32 * TP + ks * 32);
      }
      if (k2 == 1) anchors();
#pragma unroll
      for (int k = 0; k < 2; k++)
#pragma unroll
        for (int t = 0; t < 5; t++) hmma(acc[t], fa[k][0], fa[k][1], fa[k][2], fa[k][3], fb[k][2 * t], fb[k][2 * t + 1]);
    }
    __syncwarp();
  }
  TR(45);
#pragma unroll
  for (int s = 16; s > 0; s >>= 1) k0 += __shfl_xor_sync(0xffffffffu, k0, s);
  k0 += __bfloat162float(*dskip);
  const uint32_t kh = ws + W_KD + warp * KDP + 2 * KR_T + 1024;
  const uint32_t kd = kh - 1024 + KDH;
  sts16(kh - 1022 + 2 * lane, 0);
  sts16(kd + 2 + 2 * lane, 0);
  for (int i = lane; i < 43; i += 32) sts16(kh - 2 * (1029 + i), 0);
  for (int i = lane; i < 48; i += 32) sts16(kd - 2 * (512 + i), 0);
  if (lane == 0) sts16(kd, pack2(k0, 0.f));
#pragma unroll
  for (int h = 0; h < 2; h++) {
    const int j = g + 8 * h;
    const bool edge = h == 1 && lane == 31;
    const uint32_t t0 = pack2(acc[0][2 * h], acc[0][2 * h + 1]), t1 = pack2(acc[1][2 * h], acc[1][2 * h + 1]);
    const uint32_t t2 = pack2(acc[2][2 * h], acc[2][2 * h + 1]), t3 = pack2(acc[3][2 * h], acc[3][2 * h + 1]);
    const uint32_t t4 = pack2(acc[4][2 * h], acc[4][2 * h + 1]);
    const uint32_t q0 = kd - 2 * (1 + 2 * c + 8 * j);
    sts16(q0, t0); sts16(q0 - 2, t0 >> 16);
    sts16(q0 - 256, t1); sts16(q0 - 258, t1 >> 16);
    const uint32_t q2 = kd - 2 * (258 + 4 * (c & 1) + 128 * (c >> 1) + 8 * j);
    const uint32_t q2u = edge ? kh - 2 * 510 : q2;
    sts16(q2, t2); sts16(q2 - 2, t2 >> 16); sts16(q2u - 4, t2 >> 16); sts16(q2u - 6, t2 >> 16);
    const uint32_t q3 = kh - 2 * (516 + 128 * c + 8 * j);
    sts16(q3 + 2, t3); sts16(q3, t3); sts16(q3 - 2, t3);
#pragma unroll
    for (int k = 2; k <= 6; k++) sts16(q3 - 2 * k, t3 >> 16);
    const uint32_t q4 = ws + W_KC + warp * 256 + 2 * (32 * c + j);
    sts16(q4, t4); sts16(q4 + 32, t4 >> 16);
    if (edge) {
      sts16(kd - 2 * 257, t1 >> 16); sts16(kh - 2 * 514, t2 >> 16);
      sts16(kh - 2 * 1027, t3 >> 16); sts16(kh - 2 * 1028, t3 >> 16);
    }
  }
}

__device__ __forceinline__ void conv_init(uint32_t ws, int tid, int barid) {
  fence_async_smem();
  bar_sync(barid, 128);
  if (tid < 72) sts128(ws + W_X + 4096 + tid * 16, 0, 0, 0, 0);
  else if (tid < 75) sts128(swz(ws + W_S7 + (tid - 72) * 16), 0, 0, 0, 0);
  else if (tid < 78) sts128(swz(ws + W_S9 + (tid - 75) * 16), 0, 0, 0, 0);
  if (tid < 40) {
#pragma unroll
    for (int e = 0; e < 4; e++) sts128(ws + W_H + e * 1152 + 512 + tid * 16, 0, 0, 0, 0);
  }
  bar_sync(barid, 128);
}

__device__ __forceinline__ void conv_prep(uint32_t ws, int tid, int t, int ch, uint32_t xbar, uint32_t xpar) {
  ws = opaque(ws);
  tid = opaque(tid);
  if (tid == 0) {
    fence_async_global();
    mbar_expect_tx(xbar, 4096);
    bulk_g2s(ws + W_X, g_xt + (size_t)ch * 256, 4096, xbar);
  }
  if (tid < 112) {
    const int seg = tid / 28, row = tid - seg * 28, hi = row >= 14, cls = row - 14 * hi;
    const int m0 = KR_T - 8 * (18 * seg - 2) - (cls - 6);
    const uint32_t src = ws + W_KD + t * KDP + (hi ? 0 : KDH) + (m0 >> 1) * 4, sel = (m0 & 1) ? 0x5432u : 0x3210u;
    const uint32_t dst = ws + W_Q + row * QP + seg * 72;
    uint32_t q[18];
#pragma unroll
    for (int i = 0; i < 18; i++) q[i] = __byte_perm(lds32_f(src - i * 16), lds32_f(src - i * 16 + 4), sel);
#pragma unroll
    for (int i = 0; i < 9; i++) sts64(dst + i * 8, q[2 * i], q[2 * i + 1]);
  }
  TR(40);
  {
    const int e = (tid >> 5) + 1, tt = tid & 31;
    const uint32_t kc = ws + W_KC + t * 256 + 2 * (123 + e - 4 * tt);
    uint32_t v[8];
#pragma unroll
    for (int s = 0; s < 8; s++) v[s] = (tt + s <= 31) ? lds16_f(kc - 8 * s) : 0u;
    sts128(ws + W_H + (e - 1) * 1152 + tt * 16, v[0] | (v[1] << 16), v[2] | (v[3] << 16), v[4] | (v[5] << 16), v[6] | (v[7] << 16));
  }
  TR(42);
  mbar_wait(xbar, xpar);
  TR(43);
  {
    float xv[16];
    uint32_t w[12];
#pragma unroll
    for (int k = 0; k < 3; k++) {
      const int n = tid + 2 + k;
      lds128(w[4 * k], w[4 * k + 1], w[4 * k + 2], w[4 * k + 3], swz(ws + W_X + (64 - (n >> 2)) * 64 + (n & 3) * 16));
    }
#pragma unroll
    for (int i = 0; i < 8; i++) {
      xv[2 * i] = bf_lo(w[2 + i]);
      xv[2 * i + 1] = bf_hi(w[2 + i]);
    }
    float s7[8], s9[8];
    s7[0] = ((xv[1] + xv[2]) + (xv[3] + xv[4])) + ((xv[5] + xv[6]) + xv[7]);
#pragma unroll
    for (int i = 1; i < 8; i++) s7[i] = s7[i - 1] + (xv[i + 7] - xv[i]);
#pragma unroll
    for (int i = 0; i < 8; i++) s9[i] = s7[i] + (xv[i] + xv[i + 8]);
    sts128(swz(ws + W_S7 + (tid + 3) * 16), pack2(s7[0], s7[1]), pack2(s7[2], s7[3]), pack2(s7[4], s7[5]), pack2(s7[6], s7[7]));
    sts128(swz(ws + W_S9 + (tid + 3) * 16), pack2(s9[0], s9[1]), pack2(s9[2], s9[3]), pack2(s9[4], s9[5]), pack2(s9[6], s9[7]));
  }
  fence_async_smem();
}

__device__ __forceinline__ void weight_box(int u, int half, int sl, int& which, int& c0, int& c1) {
  const int pass = u / 9, pos = u - pass * 9;
  if (pass < 9) {
    which = half;
    c0 = sl * 576 + pass * 64;
    c1 = pos * 64;
  } else {
    const int kc = pos == 0 ? 8 : (pos <= 2 ? pos + 5 : pos - 3);
    const int pp = pass - 9;
    const int blk = pp == 4 ? sl : ((pp == 0 && half == 0) ? 8 : ((sl + 2 * pp + half) & 7));
    which = 2;
    c0 = blk * 64;
    c1 = sl * 576 + kc * 64;
  }
}

__global__ void __launch_bounds__(512, 1)
    fused_kernel(const __grid_constant__ CUtensorMap map_w1, const __grid_constant__ CUtensorMap map_w3,
                 const __grid_constant__ CUtensorMap map_w2, const __grid_constant__ CUtensorMap map_x, const Params p) {
  extern __shared__ __align__(1024) uint8_t smem_raw[];
  const uint32_t sb = (smem_u32(smem_raw) + 1023) & ~1023u;
  const uint32_t bars = sb + OFF_BAR;
  const int wg = __shfl_sync(0xffffffffu, threadIdx.x >> 7, 0);
  const int warp = __shfl_sync(0xffffffffu, (threadIdx.x >> 5) & 3, 0);
  const int bid = blockIdx.x;
  const bool spare = bid >= 128;
  const int rank = bid & 1, pair = bid >> 1;
  const int mt = 2 * (pair & 7) + rank, sl = (pair >> 3) & 7;

  TR(0);
  KParams kp;
  if (wg == 1 || spare) {
    const int ch = (spare ? 128 + (bid - 128) * 4 + wg : bid) * 4 + warp;
    const size_t o = (size_t)ch * NM_ + (threadIdx.x & 31) * 4;
    kp.are = __ldg(reinterpret_cast<const uint2*>(p.a_re + o)); kp.aim = __ldg(reinterpret_cast<const uint2*>(p.a_im + o));
    kp.bre = __ldg(reinterpret_cast<const uint2*>(p.b_re + o)); kp.bim = __ldg(reinterpret_cast<const uint2*>(p.b_im + o));
    kp.cre = __ldg(reinterpret_cast<const uint2*>(p.c_re + o)); kp.cim = __ldg(reinterpret_cast<const uint2*>(p.c_im + o));
    kp.ldt = p.log_dt[ch];
  }
  if (threadIdx.x == 0) {
    if (!spare) {
      for (int i = 0; i < 9; i++) mbar_init(bars + B_XFULL + 8 * i, 1);
      fence_async_smem();
#pragma unroll
      for (int b = 0; b < 9; b++) {
        mbar_expect_tx(bars + B_XFULL + 8 * b, 16384);
        const uint32_t dst = b == 0 ? OFF_HS : (b <= 2 ? OFF_XS + (b - 1) * 16384 : (b == 3 ? OFF_HS + 16384 : (b - 2) * STAGE));
        tma2d(sb + dst, &map_x, b * 64, mt * 128, bars + B_XFULL + 8 * b);
      }
      asm volatile("prefetch.tensormap [%0];" ::"l"(&map_w1) : "memory");
      asm volatile("prefetch.tensormap [%0];" ::"l"(&map_w3) : "memory");
      asm volatile("prefetch.tensormap [%0];" ::"l"(&map_w2) : "memory");
    }
  } else if (threadIdx.x == 32) {
    for (int i = 0; i < NST; i++) {
      mbar_init(bars + B_FULL + 8 * i, 1);
      mbar_init(bars + B_EMPTY + 8 * i, 4);
    }
    for (int i = 0; i < 8; i++) mbar_init(bars + B_PART + 8 * i, 128);
    mbar_init(bars + B_XFREE, 16);
    mbar_init(bars + B_XROW, 1);
    mbar_init(bars + B_RST, 96);
    for (int i = 0; i < 5; i++) mbar_init(bars + B_FET + 8 * i, 1);
    for (int i = 0; i < 4; i++) mbar_init(bars + B_FREE + 8 * i, 128);
    mbar_init(bars + B_STATS, 9);
    mbar_init(bars + B_PRESUM, 128);
    mbar_init(bars + B_LAG, 1);
    for (int i = 0; i < 4; i++) {
      mbar_init(bars + B_XCH + 8 * i, 1);
      mbar_init(bars + B_CREADY + 8 * i, 128);
      mbar_init(bars + B_CDONE + 8 * i, 128);
    }
    asm volatile("fence.mbarrier_init.release.cluster;" ::: "memory");
    fence_async_smem();
  }
  __syncthreads();
  asm volatile("barrier.cluster.arrive.relaxed.aligned;\nbarrier.cluster.wait.aligned;" ::: "memory");
#define ep lds32(bars + B_EPOCH)
  TR(1);

  if (wg == 0 && !spare) {
    asm volatile("setmaxnreg.dec.sync.aligned.u32 24;");
    const int lane = tid_now() & 31;
    if (warp == 0) {
      if (lane == 0) {
        int st = 0;
        uint32_t ph = 1;
#pragma unroll 1
        for (int u = 2 + ((pair + 6) & 7); u < PFD; u += 8) {
          int which, c0, c1;
          weight_box(u, rank, sl, which, c0, c1);
          tma2d_prefetch(which == 0 ? &map_w1 : &map_w3, c0, c1);
        }
#pragma unroll 1
        for (int u = 0; u < 126; u++) {
          if (u == 2) mbar_wait(bars + B_XFREE, 0);
          if (u >= NST) mbar_wait(bars + B_EMPTY + 8 * st, ph);
          const bool last = u >= 117;
          mbar_expect_tx(bars + B_FULL + 8 * st, last ? 8192 : 16384);
          if (!last || ((u - 117) & 1) == rank) {
            int which, c0, c1;
            weight_box(u, rank, sl, which, c0, c1);
            const CUtensorMap* m = which == 0 ? &map_w1 : (which == 1 ? &map_w3 : &map_w2);
            tma2d_mc(sb + st * STAGE + (last ? 0 : rank * 8192), m, c0, c1, bars + B_FULL + 8 * st);
          }
          if (((u + PFD) & 7) == (pair & 7) && u + PFD < 126) {
            int which, c0, c1;
            weight_box(u + PFD, rank, sl, which, c0, c1);
            tma2d_prefetch(which == 0 ? &map_w1 : (which == 1 ? &map_w3 : &map_w2), c0, c1);
          }
          if (++st == NST) { st = 0; ph ^= 1; }
        }
        asm volatile("barrier.cluster.arrive.relaxed;\nbarrier.cluster.wait;" ::: "memory");
      }
    } else {
      {
        if (warp == 3 && lane == 0) {
          sts32(bars + B_EPOCH, ldg32_cg(&g_epoch) + 1u);
          mbar_arrive(bars + B_STATS);
        }
        if (warp == 1) {
          mbar_wait(bars + B_XFREE, 0);
          if (lane == 0) mbar_expect_tx(bars + B_XROW, 16 * 1152);
          __syncwarp();
          if (lane < 16) bulk_g2s(sb + OFF_HS + lane * 1168, p.x + (size_t)(mt * 128 + sl * 16 + lane) * D_, 1152, bars + B_XROW);
        }
#pragma unroll 1
        for (int i = (warp - 1) * 32 + lane; i < 2048; i += 96)
          stg128(g_part + (size_t)((mt * 9 + sl) * 8 + ((sl + 1 + (i >> 10)) & 7)) * 1024 + (i & 1023), EMPTY, EMPTY, EMPTY, EMPTY);
        mbar_arrive(bars + B_RST);
        mbar_wait(bars + B_STATS, 0);
      }
      if (warp == 3) {
        const uint32_t ws = sb + OFF_W;
        const int w8 = sl >> 2, wp = sl & 3;
        const uint4* inbox = g_part + (size_t)(mt * 9 + sl) * 8 * 1024;
        flag_wait(lane < 16 ? &g_fy[128 + lane] : &g_fy[sl * 16 + lane - 16], ep);
        mbar_wait(bars + B_FREE, 0);
        fence_async_global();
        if (lane == 0) {
          mbar_expect_tx(bars + B_FET, 32768 + 2048);
          tma2d(ws, &map_x, sl * 64, mt * 128, bars + B_FET);
          bulk_g2s(ws + 16384, g_y + ((size_t)(2 * mt) * 144 + sl * 16) * 32, 8192, bars + B_FET);
          bulk_g2s(ws + 24576, g_y + ((size_t)(2 * mt + 1) * 144 + sl * 16) * 32, 8192, bars + B_FET);
        }
        __syncwarp();
        if (lane < 16) bulk_g2s(ws + 32768 + lane * 128, g_y + ((size_t)(2 * mt + w8) * 144 + 128 + lane) * 32 + wp * 8, 128, bars + B_FET);
        TRX(8);
        if (lane < 12)
          flag_wait(lane < 8 ? &g_fp[((mt * 8 + lane) * 2 + w8) * 4] : &g_fp[((mt * 8 + (lane < 10 ? (sl - 1) & 7 : sl)) * 2 + (lane & 1)) * 4], ep);
        mbar_wait(bars + B_FREE + 8, 0);
        fence_async_global();
        if (lane == 0) {
          mbar_expect_tx(bars + B_FET + 8, 16384);
          mbar_expect_tx(bars + B_FET + 16, 16384);
          bulk_g2s(ws + 32768, inbox + ((sl - 1) & 7) * 1024, 16384, bars + B_FET + 16);
        }
        __syncwarp();
        bulk_g2s(ws + lane * 512, g_part + ((size_t)((mt * 9 + 8) * 8 + (lane >> 2)) * 2 + w8) * 512 + (lane & 3) * 128 + wp * 32, 512, bars + B_FET + 8);
        TRX(9);
#pragma unroll 1
        for (int pp = 1; pp < 3; pp++) {
          if (lane < 4) flag_wait(&g_fp[((mt * 8 + ((sl - 2 * pp - (lane >> 1)) & 7)) * 2 + (lane & 1)) * 4 + pp], ep);
          mbar_wait(bars + B_FREE + 8 + 8 * pp, 0);
          fence_async_global();
          if (lane == 0) mbar_expect_tx(bars + B_FET + 16 + 8 * pp, 32768);
          __syncwarp();
          if (lane < 2) bulk_g2s(ws + lane * 16384, inbox + ((sl - 2 * pp - lane) & 7) * 1024, 16384, bars + B_FET + 16 + 8 * pp);
          TRX(21 + pp);
        }
      } else {
#pragma unroll 1
        for (int pp = 0; pp < 3; pp++) {
          mbar_wait(bars + B_PART + 32 * (warp - 1) + 8 * pp, 0);
          if (lane < 2) flag_set(&g_fp[((mt * 8 + sl) * 2 + (warp - 1)) * 4 + pp], ep, lane);
          __syncwarp();
        }
      }
    }
  } else if (spare) {
    const int tid = tid_now() & 127, lane = tid & 31;
    const uint32_t ws = sb + wg * W_STRIDE;
    const int grp = 128 + (bid - 128) * 4 + wg;
    unsigned ep0 = 0;
    if (warp == 0) ep0 = ldg32_cg(&g_epoch) + 1u;
    kgen(kp, p.dskip + grp * 4 + warp, ws, warp, lane);
    TR(2);
    if (warp == 0) {
#pragma unroll 1
      for (int k = 0; k < 4; k++) flag_wait(&g_fx[k * 32 + lane], ep0);
    }
    TR(3);
    conv_init(ws, tid, wg + 1);
    uint32_t yk[4][8];
#pragma unroll 1
    for (int t = 0; t < 4; t++) {
      TR(4 + 2 * t);
      conv_prep(ws, tid, t, grp * 4 + t, bars + B_XCH + 8 * wg, t & 1);
      TR(5 + 2 * t);
      bar_sync(wg + 1, 128);
      conv_mma<3, 3>(ws, warp, lane);
      bar_sync(wg + 1, 128);
      conv_out(ws, warp, lane, yk[t]);
    }
    conv_store(yk, warp, lane, grp);
    bar_sync(wg + 1, 128);
    TR(12);
    if (tid < 2) flag_set(&g_fy[grp], ep0, tid);
  } else if (wg == 1) {
    asm volatile("setmaxnreg.dec.sync.aligned.u32 72;");
    const int tid = tid_now() & 127, lane = tid & 31;
    const int g = lane >> 2, c = lane & 3;
    const uint32_t ws = sb + OFF_W;
    kgen(kp, p.dskip + bid * 4 + warp, ws, warp, lane);
    mbar_wait(bars + B_STATS, 0);
    TR(2);
    {
      const int rho = 63 - 4 * mt - (sl >> 1);
      uint4* dst = g_xt + (size_t)(warp * 144 + (lane >> 1)) * 256 + rho * 4 + ((2 * (sl & 1) + (lane & 1)) ^ ((rho >> 1) & 3));
      const uint32_t src = sb + OFF_HS + (lane & 15) * 1168 + warp * 288 + (lane >> 4) * 16;
      const uint32_t stg = sb + OFF_HS + 18688 + warp * 1536;
      uint32_t m2a, rha, rla, m2b, rhb, rlb;
      {
        uint32_t m0, r0, m1, r1;
        lds128(m0, r0, m1, r1, sb + OFF_STAT + (sl * 16 + 2 * c) * 8);
        m2a = pack2(__uint_as_float(m0), __uint_as_float(m1));
        rha = pack2(__uint_as_float(r0), __uint_as_float(r1));
        rla = pack2(__uint_as_float(r0) - bf_lo(rha), __uint_as_float(r1) - bf_hi(rha));
        lds128(m0, r0, m1, r1, sb + OFF_STAT + (sl * 16 + 2 * c + 8) * 8);
        m2b = pack2(__uint_as_float(m0), __uint_as_float(m1));
        rhb = pack2(__uint_as_float(r0), __uint_as_float(r1));
        rlb = pack2(__uint_as_float(r0) - bf_lo(rhb), __uint_as_float(r1) - bf_hi(rhb));
      }
      mbar_wait(bars + B_XROW, 0);
#pragma unroll 1
      for (int k3 = 0; k3 < 3; k3++) {
        uint32_t x[3][4];
#pragma unroll
        for (int k = 0; k < 3; k++) ldsm4t(x[k][0], x[k][1], x[k][2], x[k][3], src + (3 * k3 + k) * 32);
        __syncwarp();
#pragma unroll
        for (int k = 0; k < 3; k++)
          stsm4(stg + k * 512 + ((lane & 7) + 8 * (lane >> 4)) * 32 + ((lane >> 3) & 1) * 16, hnorm2(hsub2(x[k][0], m2a), rha, rla),
                hnorm2(hsub2(x[k][1], m2b), rhb, rlb), hnorm2(hsub2(x[k][2], m2a), rha, rla), hnorm2(hsub2(x[k][3], m2b), rhb, rlb));
        __syncwarp();
#pragma unroll
        for (int k = 0; k < 3; k++) {
          lds128(x[k][0], x[k][1], x[k][2], x[k][3], stg + k * 512 + lane * 16);
          stg128(dst + (3 * k3 + k) * 4096, x[k][0], x[k][1], x[k][2], x[k][3]);
        }
      }
      TR(20);
      mbar_wait(bars + B_RST, 0);
      bar_sync(2, 128);
      if (tid < 2) flag_set(&g_fx[bid], ep, tid);
      __syncwarp();
      TR(21);
    }
    if (warp == 0) {
#pragma unroll 1
      for (int k = 0; k < 4; k++) flag_wait(&g_fx[k * 32 + lane], ep);
    }
    TR(3);
    conv_init(ws, tid, 2);
    uint32_t yk[4][8];
#pragma unroll 1
    for (int t = 0; t < 4; t++) {
      TR(4 + 2 * t);
      conv_prep(ws, tid, t, bid * 4 + t, bars + B_XCH + 8, t & 1);
      TR(5 + 2 * t);
      mbar_arrive(bars + B_CREADY + 8 * t);
      mbar_wait(bars + B_CDONE + 8 * t, 0);
      conv_out(ws, warp, lane, yk[t]);
    }
    conv_store(yk, warp, lane, bid);
    bar_sync(2, 128);
    TR(12);
    if (tid < 2) flag_set(&g_fy[bid], ep, tid);
    {
      const uint32_t lm = frag_off(tid);
      mbar_arrive(bars + B_FREE);
      uint32_t x8[4];
#pragma unroll
      for (int i = 0; i < 4; i++)
        x8[i] = __ldg(reinterpret_cast<const uint32_t*>(p.x) + (size_t)(mt * 128 + sl * 16 + g + 8 * (i & 1)) * (D_ / 2) + 256 + 4 * (2 * warp + (i >> 1)) + c);
      mbar_wait(bars + B_FET, 0);
      TR(13);
      uint32_t bs[32];
#pragma unroll
      for (int k = 0; k < 8; k++) {
        uint32_t x0, x1, x2, x3;
        ldsm4(x0, x1, x2, x3, ws + (k >> 2) * 8192 + (lm ^ ((k & 3) << 5)));
        const uint32_t ya = ws + 16384 + (k >> 2) * 8192 + (4 * (k & 3) + (c >> 1)) * 512 + warp * 128 + g * 8 + (c & 1) * 4;
        bs[4 * k] = hadd2(x0, lds32(ya));
        bs[4 * k + 1] = hadd2(x1, lds32(ya + 64));
        bs[4 * k + 2] = hadd2(x2, lds32(ya + 1024));
        bs[4 * k + 3] = hadd2(x3, lds32(ya + 1024 + 64));
      }
#pragma unroll
      for (int i = 0; i < 4; i++)
        x8[i] = hadd2(x8[i], lds32(ws + 32768 + (2 * (2 * warp + (i >> 1)) + (c >> 1)) * 128 + (i & 1) * 64 + g * 8 + (c & 1) * 4));
      mbar_arrive(bars + B_FREE + 8);
      TR(14);
      mbar_wait(bars + B_FET + 8, 0);
      {
        const float ra = __uint_as_float(lds32(sb + OFF_STAT + (sl * 16 + g) * 8 + 4)), rb = __uint_as_float(lds32(sb + OFF_STAT + (sl * 16 + g) * 8 + 68));
        float s[8];
#pragma unroll
        for (int i = 0; i < 8; i++) s[i] = 0.f;
#pragma unroll
        for (int src = 0; src < 8; src++) {
          uint32_t v0, v1, v2, v3;
          lds128(v0, v1, v2, v3, ws + src * 2048 + tid * 16);
          s[0] += bf_lo(v0); s[1] += bf_hi(v0); s[2] += bf_lo(v1); s[3] += bf_hi(v1);
          s[4] += bf_lo(v2); s[5] += bf_hi(v2); s[6] += bf_lo(v3); s[7] += bf_hi(v3);
        }
        const uint32_t sg = ws + warp * 512;
        uint32_t o0 = pack2(fmaf(ra, s[0], bf_lo(x8[0])), fmaf(ra, s[1], bf_hi(x8[0]))), o1 = pack2(fmaf(rb, s[2], bf_lo(x8[1])), fmaf(rb, s[3], bf_hi(x8[1])));
        uint32_t o2 = pack2(fmaf(ra, s[4], bf_lo(x8[2])), fmaf(ra, s[5], bf_hi(x8[2]))), o3 = pack2(fmaf(rb, s[6], bf_lo(x8[3])), fmaf(rb, s[7], bf_hi(x8[3])));
        __syncwarp();
        stsm4(sg + (lane & 15) * 32 + (lane >> 4) * 16, o0, o1, o2, o3);
        __syncwarp();
        lds128(o0, o1, o2, o3, sg + lane * 16);
        fence_async_smem();
        mbar_arrive(bars + B_FREE + 16);
        stg128(p.out + (size_t)(mt * 128 + sl * 16 + (lane >> 1)) * D_ + 512 + warp * 16 + (lane & 1) * 8, o0, o1, o2, o3);
      }
      TR(15);
      float rr[4];
#pragma unroll
      for (int i = 0; i < 4; i++) rr[i] = __uint_as_float(lds32(sb + OFF_STAT + ((i >> 1) * 64 + warp * 16 + g + 8 * (i & 1)) * 8 + 4));
      mbar_wait(bars + B_FET + 16, 0);
      mbar_wait(bars + B_FET + 24, 0);
      TR(16);
#pragma unroll
      for (int k = 0; k < 8; k++) {
        uint32_t u[4], v[4], t[4];
        lds128(u[0], u[1], u[2], u[3], ws + k * 2048 + tid * 16);
        lds128(v[0], v[1], v[2], v[3], ws + 16384 + k * 2048 + tid * 16);
        lds128(t[0], t[1], t[2], t[3], ws + 32768 + k * 2048 + tid * 16);
        uint32_t o[8];
#pragma unroll
        for (int i = 0; i < 4; i++) {
          const float r = rr[2 * (k >> 2) + (i & 1)];
          o[2 * i] = __float_as_uint(fmaf(r, bf_lo(u[i]) + bf_lo(v[i]) + bf_lo(t[i]), bf_lo(bs[4 * k + i])));
          o[2 * i + 1] = __float_as_uint(fmaf(r, bf_hi(u[i]) + bf_hi(v[i]) + bf_hi(t[i]), bf_hi(bs[4 * k + i])));
        }
        const uint32_t a = sb + OFF_XS + ((2 * (k & 3)) * 256 + (k >> 2) * 128 + tid) * 16;
        sts128(a, o[0], o[1], o[2], o[3]);
        sts128(a + 4096, o[4], o[5], o[6], o[7]);
      }
      mbar_arrive(bars + B_FREE + 24);
      TR(17);
      mbar_wait(bars + B_FET + 32, 0);
      TR(19);
#pragma unroll 2
      for (int k = 0; k < 8; k++) {
        uint32_t u[4], v[4], b[8];
        const uint32_t a = sb + OFF_XS + ((2 * (k & 3)) * 256 + (k >> 2) * 128 + tid) * 16;
        lds128(u[0], u[1], u[2], u[3], ws + k * 2048 + tid * 16);
        lds128(v[0], v[1], v[2], v[3], ws + 16384 + k * 2048 + tid * 16);
        lds128(b[0], b[1], b[2], b[3], a);
        lds128(b[4], b[5], b[6], b[7], a + 4096);
        const float ra = k < 4 ? rr[0] : rr[2], rb = k < 4 ? rr[1] : rr[3];
#pragma unroll
        for (int i = 0; i < 4; i++) {
          const float r = (i & 1) ? rb : ra;
          b[2 * i] = __float_as_uint(fmaf(r, bf_lo(u[i]) + bf_lo(v[i]), __uint_as_float(b[2 * i])));
          b[2 * i + 1] = __float_as_uint(fmaf(r, bf_hi(u[i]) + bf_hi(v[i]), __uint_as_float(b[2 * i + 1])));
        }
        sts128(a, b[0], b[1], b[2], b[3]);
        sts128(a + 4096, b[4], b[5], b[6], b[7]);
      }
      mbar_arrive(bars + B_PRESUM);
      TR(18);
      if (bid == 0 && tid == 0) *(volatile unsigned*)&g_epoch = ep;
    }
  } else {
    asm volatile("setmaxnreg.inc.sync.aligned.u32 208;");
    const int w = wg - 2;
    uint32_t a[112];
    {
      uint32_t t[32];
      const uint32_t tl = tid_now(), lm = frag_off(tl);
      const int lane = tl & 31;
      float s0[4] = {0.f, 0.f, 0.f, 0.f}, qa[4] = {0.f, 0.f, 0.f, 0.f}, qb[4] = {0.f, 0.f, 0.f, 0.f};
      const uint32_t ONE = 0x3f803f80u;
#pragma unroll
      for (int b = 0; b < 9; b++) {
        mbar_wait(bars + B_XFULL + 8 * b, 0);
        const uint32_t src = sb + (b == 0 ? OFF_HS : (b <= 2 ? OFF_XS + (b - 1) * 16384 : (b == 3 ? OFF_HS + 16384 : (b - 2) * STAGE)));
        uint32_t tb[16];
#pragma unroll
        for (int kk = 0; kk < 4; kk++) {
          uint32_t* r = (b == 0) ? &a[4 * kk] : (b <= 2 ? &t[16 * (b - 1) + 4 * kk] : &a[16 * (b - 2) + 4 * kk]);
          ldsm4(r[0], r[1], r[2], r[3], src + (lm ^ (kk << 5)));
        }
        if (b == 8) {
          __syncwarp();
          if (lane < 2) mbar_arrive_cl(mapa(bars + B_XFREE, lane));
          mbar_wait(bars + B_XFULL, 0);
        }
#pragma unroll
        for (int kk = 0; kk < 4; kk++) {
          uint32_t* r = (b == 0) ? &a[4 * kk] : (b <= 2 ? &t[16 * (b - 1) + 4 * kk] : &a[16 * (b - 2) + 4 * kk]);
          tb[4 * kk] = vmov(r[0]); tb[4 * kk + 1] = vmov(r[2]); tb[4 * kk + 2] = vmov(r[1]); tb[4 * kk + 3] = vmov(r[3]);
        }
#pragma unroll
        for (int kk = 0; kk < 4; kk++) {
          uint32_t* r = (b == 0) ? &a[4 * kk] : (b <= 2 ? &t[16 * (b - 1) + 4 * kk] : &a[16 * (b - 2) + 4 * kk]);
          hmma(s0, r[0], r[1], r[2], r[3], ONE, ONE);
          hmma(qa, r[0], r[1], r[2], r[3], tb[4 * kk], tb[4 * kk + 1]);
          hmma(qb, r[0], r[1], r[2], r[3], tb[4 * kk + 2], tb[4 * kk + 3]);
        }
      }
      TR(2);
      const float meana = s0[0] * (1.f / D_), meanb = s0[2] * (1.f / D_);
      const float mba = bf_round(meana), mbb = bf_round(meanb);
      const uint32_t m2a = pack2(mba, mba), m2b = pack2(mbb, mbb);
#pragma unroll
      for (int ks = 0; ks < 8; ks++) {
        uint32_t* r = &t[4 * ks];
        stsm4(sb + OFF_XS + (ks >> 2) * 16384 + (lm ^ ((ks & 3) << 5)), hsub2(r[0], m2a), hsub2(r[1], m2b), hsub2(r[2], m2a), hsub2(r[3], m2b));
      }
      fence_async_smem();
      {
        const int g = lane >> 2;
        const uint32_t sa = sb + OFF_STAT + stat_off(tl);
        if ((lane & 3) == (g >> 1)) {
          sts64(sa, __float_as_uint(mba), __float_as_uint(fmaxf(fmaf(-meana, meana, ((g & 1) ? qa[1] : qa[0]) * (1.f / D_)), 0.f)));
          sts64(sa + 64, __float_as_uint(mbb), __float_as_uint(fmaxf(fmaf(-meanb, meanb, ((g & 1) ? qb[3] : qb[2]) * (1.f / D_)), 0.f)));
        }
      }
      mbar_wait(bars + B_XFULL, 0);
      TR(48);
#pragma unroll
      for (int ks = 0; ks < 28; ks++) {
        uint32_t* r = &a[4 * ks];
        r[0] = hsub2(r[0], m2a); r[1] = hsub2(r[1], m2b); r[2] = hsub2(r[2], m2a); r[3] = hsub2(r[3], m2b);
      }
      TR(49);
      bar_sync(6 + w, 128);
    }
    const bool rel = (tid_now() & 0x5f) == 0;
    const uint32_t ebar = mapa(bars + B_EMPTY, warp & 1);
    const uint64_t dB = make_desc(sb, 8192, 1024, 1);
    int st = 0;
    uint32_t ph = 0, lagp = 0;
    auto finish_stats = [&]() {
      const uint32_t t = tid_now();
      if ((t & 31) < 16) {
        const uint32_t sa = sb + OFF_STAT + (((t & 0xe0u) >> 1) + (t & 15)) * 8 + 4;
        sts32(sa, __float_as_uint(rcp_ap(bf_round(sqrt_ap(bf_round(bf_round(__uint_as_float(lds32(sa))) + 1e-5f))))));
      }
      __syncwarp();
      if ((t & 31) == 0) mbar_arrive(bars + B_STATS);
    };
    auto tile128 = [&](float (&acc)[64], const uint64_t dA, const bool first, auto reload) {
      int pst = 0;
      if (w == 1) {
        if (first) finish_stats();
        mbar_wait(bars + B_LAG, lagp);
      }
      lagp ^= 1;
#pragma unroll
      for (int pos = 0; pos < 9; pos++) {
        mbar_wait(bars + B_FULL + 8 * st, ph);
        wg_fence();
        const uint64_t d = dB + (uint64_t)(st * (STAGE >> 4));
#pragma unroll
        for (int kk = 0; kk < 4; kk++) {
          if (pos == 1 || pos == 2) mma_n128_ss(acc, dA + (uint64_t)((pos - 1) * 1024 + kk * 2), d + kk * 128, 1);
          else {
            const int o = (pos == 0 ? 0 : 16 * (pos - 2)) + 4 * kk;
            mma_n128_rs(acc, a[o], a[o + 1], a[o + 2], a[o + 3], d + kk * 128, (pos | kk) != 0);
          }
        }
        wg_commit();
        if (pos > 0) {
          wg_wait<1>();
          if (rel) mbar_arrive_cl(ebar + 8 * pst);
        }
        if (pos == 0 && first && w == 0) finish_stats();
        if (decltype(reload)::value && pos < 3) {
          const uint4* park = g_hpark + (size_t)bid * (6 * 4 * 256) + (tid_now() - 256);
#pragma unroll
          for (int q = 8 * pos; q < 8 * pos + 8; q++) {
            const uint4 v = park[q * 256];
            a[16 + 4 * q] = v.x; a[17 + 4 * q] = v.y; a[18 + 4 * q] = v.z; a[19 + 4 * q] = v.w;
          }
        }
        if (pos == LAGPOS && tid_now() == 256) mbar_arrive(bars + B_LAG);
        pst = st;
        if (++st == NST) { st = 0; ph ^= 1; }
      }
      wg_wait<0>();
      pin(acc);
      if (rel) mbar_arrive_cl(ebar + 8 * pst);
    };
    auto put_partials = [&](float (&acc)[64], const int pp) {
#pragma unroll
      for (int hb = 0; hb < 2; hb++) {
        const int blk = (pp == 0 && hb == 0) ? 8 : ((sl + 2 * pp + hb) & 7);
        uint4* dst = g_part + ((size_t)((mt * 9 + blk) * 8 + sl) * 2 + w) * 512 + (tid_now() & 127);
#pragma unroll
        for (int q = 0; q < 4; q++) {
          const float* s = &acc[32 * hb + 8 * q];
          stg128_rlx(dst + q * 128, pack2(s[0], s[1]), pack2(s[2], s[3]), pack2(s[4], s[5]), pack2(s[6], s[7]));
        }
      }
      if (pp < 3) mbar_arrive(bars + B_PART + 32 * w + 8 * pp);
    };
    TR(3);
#pragma unroll 1
    for (int pass = 0; pass < 9; pass++) {
      {
        float acc[64];
        tile128(acc, make_desc(sb + OFF_XS + w * 8192, 16, 1024, 1), pass == 0, BoolC<false>());
        TR(4 + 3 * pass);
        const uint32_t tn = tid_now();
        const float rha = 0.5f * __uint_as_float(lds32(sb + OFF_STAT + stat_off(tn) + 4));
        const float rhb = 0.5f * __uint_as_float(lds32(sb + OFF_STAT + stat_off(tn) + 68));
        uint4* const park = g_hpark + (size_t)bid * (6 * 4 * 256) + (tn - 256);
        uint32_t hp[16];
#pragma unroll
        for (int i = 0; i < 16; i++) {
          const float rh = (i & 1) ? rhb : rha;
          const float g0 = acc[2 * i] * rh, g1 = acc[2 * i + 1] * rh;
          hp[i] = pack2(fmaf(g0, tanh_ap(g0), g0) * acc[32 + 2 * i], fmaf(g1, tanh_ap(g1), g1) * acc[33 + 2 * i]);
        }
        if (pass < 6) {
#pragma unroll
          for (int q = 0; q < 4; q++) park[(pass * 4 + q) * 256] = make_uint4(hp[4 * q], hp[4 * q + 1], hp[4 * q + 2], hp[4 * q + 3]);
        } else if (pass < 8) {
#pragma unroll
          for (int q = 0; q < 4; q++) stsm4(sb + OFF_HS + (pass - 6) * 16384 + (frag_off(tn) ^ (q << 5)), hp[4 * q], hp[4 * q + 1], hp[4 * q + 2], hp[4 * q + 3]);
          fence_async_smem();
        } else {
          bar_sync(6 + w, 128);
#pragma unroll
          for (int i = 0; i < 16; i++) a[i] = hp[i];
        }
      }
      TR(5 + 3 * pass);
      if (w == 0 && ((JOBMASK >> pass) & 1)) {
        const int t = __popc(JOBMASK & ((1 << pass) - 1));
        mbar_wait(bars + B_CREADY + 8 * t, 0);
        conv_mma<2, 3>(sb + OFF_W, warp, tid_now() & 31);
        mbar_arrive(bars + B_CDONE + 8 * t);
        TR(6 + 3 * pass);
      }
    }
    const uint64_t dH = make_desc(sb + OFF_HS + w * 8192, 16, 1024, 1);
    {
      float acc[64];
      tile128(acc, dH, false, BoolC<true>());
      TR(4 + 27);
      put_partials(acc, 0);
      TR(5 + 27);
    }
#pragma unroll 1
    for (int pp = 1; pp < 4; pp++) {
      float acc[64];
      tile128(acc, dH, false, BoolC<false>());
      TR(4 + 27 + 3 * pp);
      put_partials(acc, pp);
      TR(5 + 27 + 3 * pp);
    }
    {
      float acc[32];
      int pst = 0;
      if (w == 1) mbar_wait(bars + B_LAG, lagp);
#pragma unroll
      for (int pos = 0; pos < 9; pos++) {
        mbar_wait(bars + B_FULL + 8 * st, ph);
        wg_fence();
        const uint64_t d = dB + (uint64_t)(st * (STAGE >> 4));
#pragma unroll
        for (int kk = 0; kk < 4; kk++) {
          if (pos == 1 || pos == 2) mma_n64_ss(acc, dH + (uint64_t)((pos - 1) * 1024 + kk * 2), d + kk * 128, 1);
          else {
            const int o = (pos == 0 ? 0 : 16 * (pos - 2)) + 4 * kk;
            mma_n64_rs(acc, a[o], a[o + 1], a[o + 2], a[o + 3], d + kk * 128, (pos | kk) != 0);
          }
        }
        wg_commit();
        if (pos == 1 || pos == 2) {
          wg_wait<1>();
          if (rel) mbar_arrive_cl(ebar + 8 * pst);
        }
        if (pos == 2 && tid_now() == 256) mbar_arrive(bars + B_LAG);
        pst = st;
        if (++st == NST) { st = 0; ph ^= 1; }
      }
      TR(50);
      const uint32_t tn = tid_now();
      const int tid = tn & 127, lane = tn & 31;
      uint4 v[8];
      {
        const uint4* pp = g_part + ((size_t)((mt * 9 + sl) * 8) * 2 + w) * 512 + tid;
#pragma unroll 1
        for (int it = 0; it < 4000; it++) {
          uint32_t m = 0;
#pragma unroll
          for (int k = 0; k < 2; k++)
#pragma unroll
            for (int q = 0; q < 4; q++) v[4 * k + q] = ldg128_cg(pp + ((sl + 1 + k) & 7) * 1024 + q * 128);
#pragma unroll
          for (int k = 0; k < 8; k++) m = max(max(m, max(v[k].x, v[k].y)), max(v[k].z, v[k].w));
          if (!__any_sync(0xffffffffu, m == EMPTY)) break;
        }
      }
      TR(51);
      mbar_wait(bars + B_PRESUM, 0);
      TR(52);
      wg_wait<0>();
      pin(acc);
      const float ra = __uint_as_float(lds32(sb + OFF_STAT + stat_off(tn) + 4)), rb = __uint_as_float(lds32(sb + OFF_STAT + stat_off(tn) + 68));
      uint32_t ow[16];
#pragma unroll
      for (int j = 0; j < 8; j++) {
        uint32_t b0, b1, b2, b3;
        lds128(b0, b1, b2, b3, sb + OFF_XS + (j * 256 + w * 128 + tid) * 16);
        const uint4 pa = v[j >> 1], pb = v[4 + (j >> 1)];
        const uint32_t a0 = (j & 1) ? pa.z : pa.x, a1 = (j & 1) ? pa.w : pa.y, c0 = (j & 1) ? pb.z : pb.x, c1 = (j & 1) ? pb.w : pb.y;
        ow[2 * j] = pack2(fmaf(ra, acc[4 * j] + (bf_lo(a0) + bf_lo(c0)), __uint_as_float(b0)),
                          fmaf(ra, acc[4 * j + 1] + (bf_hi(a0) + bf_hi(c0)), __uint_as_float(b1)));
        ow[2 * j + 1] = pack2(fmaf(rb, acc[4 * j + 2] + (bf_lo(a1) + bf_lo(c1)), __uint_as_float(b2)),
                              fmaf(rb, acc[4 * j + 3] + (bf_hi(a1) + bf_hi(c1)), __uint_as_float(b3)));
      }
#pragma unroll
      for (int q = 0; q < 4; q++) stsm4(sb + OFF_HS + (frag_off(tn) ^ (q << 5)), ow[4 * q], ow[4 * q + 1], ow[4 * q + 2], ow[4 * q + 3]);
      __syncwarp();
#pragma unroll
      for (int q = 0; q < 4; q++) {
        const uint32_t row = w * 64 + warp * 16 + q * 4 + (lane >> 3);
        uint32_t o0, o1, o2, o3;
        lds128(o0, o1, o2, o3, sb + OFF_HS + row * 128 + (((lane & 7) ^ (row & 7)) << 4));
        stg128(p.out + (size_t)(mt * 128 + row) * D_ + sl * 64 + (lane & 7) * 8, o0, o1, o2, o3);
      }
      TR(53);
    }
  }
}

#undef ep

typedef CUresult (*EncodeFn)(CUtensorMap*, CUtensorMapDataType, cuuint32_t, void*, const cuuint64_t*, const cuuint64_t*, const cuuint32_t*,
                             const cuuint32_t*, CUtensorMapInterleave, CUtensorMapSwizzle, CUtensorMapL2promotion, CUtensorMapFloatOOBfill);

void make_map(EncodeFn enc, CUtensorMap* m, const void* ptr, uint64_t inner, uint64_t outer, uint32_t box_outer) {
  cuuint64_t gd[2] = {inner, outer};
  cuuint64_t gs[1] = {inner * 2};
  cuuint32_t bd[2] = {64, box_outer};
  cuuint32_t es[2] = {1, 1};
  enc(m, CU_TENSOR_MAP_DATA_TYPE_BFLOAT16, 2, const_cast<void*>(ptr), gd, gs, bd, es, CU_TENSOR_MAP_INTERLEAVE_NONE, CU_TENSOR_MAP_SWIZZLE_128B,
      CU_TENSOR_MAP_L2_PROMOTION_L2_256B, CU_TENSOR_MAP_FLOAT_OOB_FILL_NONE);
}

}

extern "C" void kernel_launch(void* const* d_in, const int* in_sizes, int n_in, void* d_out, int out_size) {
  (void)in_sizes; (void)n_in; (void)out_size;
  static EncodeFn enc = nullptr;
  if (!enc) {
    void* fn = nullptr;
    cudaDriverEntryPointQueryResult q;
    cudaGetDriverEntryPoint("cuTensorMapEncodeTiled", &fn, cudaEnableDefault, &q);
    enc = (EncodeFn)fn;
    cudaFuncSetAttribute(fused_kernel, cudaFuncAttributeMaxDynamicSharedMemorySize, SMEM_BYTES);
  }
  CUtensorMap m1, m3, m2, mx;
  make_map(enc, &m1, d_in[10], F_, D_, 64);
  make_map(enc, &m3, d_in[11], F_, D_, 64);
  make_map(enc, &m2, d_in[12], D_, F_, 64);
  make_map(enc, &mx, d_in[0], D_, L_, 128);
  Params p;
  p.x = (const __nv_bfloat16*)d_in[0];
  p.a_re = (const __nv_bfloat16*)d_in[1];
  p.a_im = (const __nv_bfloat16*)d_in[2];
  p.b_re = (const __nv_bfloat16*)d_in[3];
  p.b_im = (const __nv_bfloat16*)d_in[4];
  p.c_re = (const __nv_bfloat16*)d_in[5];
  p.c_im = (const __nv_bfloat16*)d_in[6];
  p.log_dt = (const __nv_bfloat16*)d_in[7];
  p.dskip = (const __nv_bfloat16*)d_in[8];
  p.out = (__nv_bfloat16*)d_out;
  cudaLaunchConfig_t cfg = {};
  cfg.gridDim = dim3(132);
  cfg.blockDim = dim3(512);
  cfg.dynamicSmemBytes = SMEM_BYTES;
  cfg.stream = cudaStreamPerThread;
  cudaLaunchAttribute at[1];
  at[0].id = cudaLaunchAttributeClusterDimension;
  at[0].val.clusterDim.x = 2;
  at[0].val.clusterDim.y = 1;
  at[0].val.clusterDim.z = 1;
  cfg.attrs = at;
  cfg.numAttrs = 1;
  cudaLaunchKernelEx(&cfg, fused_kernel, m1, m3, m2, mx, p);
}
```

```cpp
#include <cuda_runtime.h>
#include <cuda_bf16.h>
#include <cuda.h>
#include <stdint.h>

namespace {

constexpr int L_ = 2048, D_ = 576, F_ = 4608, NM_ = 128;
constexpr int NST = 9;
#define LAGPOS 4
#define JOBMASK 0x78
#define FSPOS 0
#define RL0 0
#define XFI 7
#define PREDELAY 4500
#define PFTRY 3
#define PFDV 24
constexpr int PFD = PFDV;
constexpr uint32_t STAGE = 16384;
constexpr uint32_t OFF_XS = NST * STAGE;
constexpr uint32_t OFF_W = OFF_XS + 32768;
constexpr uint32_t OFF_HS = OFF_W, OFF_B0 = OFF_W + 16384, OFF_B1 = OFF_W + 32768;
constexpr uint32_t TP = 144;
constexpr uint32_t KDH = 1184;
constexpr uint32_t KDP = 2 * KDH;
constexpr uint32_t W_X = 0;
constexpr uint32_t W_S7 = 5248;
constexpr uint32_t W_S9 = W_S7 + 2176;
constexpr uint32_t W_H = W_S9 + 2176;
constexpr uint32_t W_A = W_H + 4608;
constexpr uint32_t W_Y = W_S7;
constexpr uint32_t W_T = 0;
constexpr uint32_t W_KC = W_A + 146 * 144;
constexpr uint32_t W_KD = W_KC + 1024;
constexpr uint32_t W_SIZE = W_KD + 4 * KDP;
constexpr uint32_t W_STRIDE = 49152;
static_assert(W_KD % 16 == 0 && KDH % 16 == 0 && W_S7 % 128 == 0 && W_H % 128 == 0 && 4 * 56 * TP <= W_KC, "alias");
constexpr uint32_t OFF_STAT = OFF_W + W_STRIDE;
constexpr uint32_t OFF_BAR = OFF_STAT + 1024;
constexpr uint32_t SMEM_BYTES = OFF_BAR + 640 + 896;
static_assert(W_SIZE + 1536 <= W_STRIDE, "workspace");
static_assert(SMEM_BYTES <= 232448, "smem");
constexpr uint32_t B_FULL = 0, B_EMPTY = 8 * NST, B_XFULL = 16 * NST, B_XFREE = B_XFULL + 72, B_STATS = B_XFREE + 8,
                   B_PRESUM = B_STATS + 8, B_LAG = B_PRESUM + 8, B_XCH = B_LAG + 8, B_CREADY = B_XCH + 32,
                   B_CDONE = B_CREADY + 32, B_PASS = B_CDONE + 32, B_FET = B_PASS + 16, B_FREE = B_FET + 32, B_EXP = B_FREE + 32,
                   B_HPK = B_EXP + 8, B_HFR = B_HPK + 8,
                   B_EPOCH = B_HFR + 8;
static_assert(B_EPOCH + 24 <= 640, "barrier area");
constexpr int KR_T = 559;

__device__ uint4 g_hpark[128 * 7 * 4 * 256];
__device__ uint4 g_part[16 * 9 * 8 * 2 * 4 * 128];
__device__ uint4 g_xt[D_ * 256];
__device__ uint4 g_y[32 * 144 * 32];
struct alignas(32) Flag {
  uint4 v[2];
};
__device__ Flag g_fx[128];
__device__ Flag g_fy[144];
__device__ unsigned g_epoch;

__device__ __forceinline__ uint32_t smem_u32(const void* p) { return (uint32_t)__cvta_generic_to_shared(p); }
__device__ __forceinline__ void mbar_init(uint32_t bar, uint32_t cnt) {
  asm volatile("mbarrier.init.shared::cta.b64 [%0], %1;" ::"r"(bar), "r"(cnt) : "memory");
}
__device__ __forceinline__ void mbar_expect_tx(uint32_t bar, uint32_t bytes) {
  asm volatile("mbarrier.arrive.expect_tx.shared::cta.b64 _, [%0], %1;" ::"r"(bar), "r"(bytes) : "memory");
}
__device__ __forceinline__ void mbar_arrive(uint32_t bar) {
  asm volatile("mbarrier.arrive.shared::cta.b64 _, [%0];" ::"r"(bar) : "memory");
}
__device__ __forceinline__ void mbar_arrive_cl(uint32_t cbar) {
  asm volatile("mbarrier.arrive.shared::cluster.b64 _, [%0];" ::"r"(cbar) : "memory");
}
__device__ __forceinline__ uint32_t mapa(uint32_t a, uint32_t cta) {
  uint32_t r;
  asm volatile("mapa.shared::cluster.u32 %0, %1, %2;" : "=r"(r) : "r"(a), "r"(cta));
  return r;
}
#define TO_NOTE
#define TO_ARG(site)
template <int SITE>
__device__ __forceinline__ void mbar_wait_(uint32_t bar, uint32_t parity) {
  asm volatile(
      "{\n.reg .pred p;\n.reg .u32 c, v;\nmov.u32 c, 0;\n"
      "LW:\nmbarrier.try_wait.parity.shared::cta.b64 p, [%0], %1;\n@p bra LD;\n"
      "add.u32 c, c, 1;\nsetp.lt.u32 p, c, 4000;\n@p bra LW;\n" TO_NOTE "LD:\n}" ::"r"(bar),
      "r"(parity) TO_ARG(SITE)
      : "memory");
}
template <int SITE>
__device__ __forceinline__ void flag_wait_(const Flag* f, unsigned ep) {
  asm volatile(
      "{\n.reg .pred p;\n.reg .u32 c, v;\nmov.u32 c, 0;\n"
      "LW:\nld.relaxed.gpu.global.u32 v, [%0];\nsetp.eq.u32 p, v, %1;\n@p bra LD;\n"
      "nanosleep.u32 200;\nadd.u32 c, c, 1;\nsetp.lt.u32 p, c, 8000;\n@p bra LW;\n" TO_NOTE "LD:\n}" ::"l"(f),
      "r"(ep) TO_ARG(SITE)
      : "memory");
}
__device__ __forceinline__ void fence_async_global() { asm volatile("fence.proxy.async.global;" ::: "memory"); }
__device__ __forceinline__ void mbar_wait_short(uint32_t bar, uint32_t parity) {
  asm volatile(
      "{\n.reg .pred p;\n.reg .u32 c;\nmov.u32 c, 0;\n"
      "LW:\nmbarrier.try_wait.parity.shared::cta.b64 p, [%0], %1;\n@p bra LD;\n"
      "add.u32 c, c, 1;\nsetp.lt.u32 p, c, %2;\n@p bra LW;\nLD:\n}" ::"r"(bar),
      "r"(parity), "n"(PFTRY)
      : "memory");
}
#define mbar_wait mbar_wait_<__COUNTER__>
#define flag_wait flag_wait_<__COUNTER__>
__device__ __forceinline__ void fence_gpu() { asm volatile("fence.acq_rel.gpu;" ::: "memory"); }
__device__ __forceinline__ void flag_set(Flag* f, unsigned ep, int lane) {
  asm volatile("fence.acq_rel.gpu;\nst.relaxed.gpu.global.v4.u32 [%0], {%1,%1,%1,%1};" ::"l"(&f->v[lane]), "r"(ep) : "memory");
}
__device__ __forceinline__ void bar_sync(int id, int n) { asm volatile("bar.sync %0, %1;" ::"r"(id), "r"(n) : "memory"); }
__device__ __forceinline__ void fence_async_smem() { asm volatile("fence.proxy.async.shared::cta;" ::: "memory"); }
__device__ __forceinline__ void tma2d(uint32_t dst, const CUtensorMap* m, int c0, int c1, uint32_t bar) {
  asm volatile("cp.async.bulk.tensor.2d.shared::cluster.global.mbarrier::complete_tx::bytes [%0], [%1, {%3, %4}], [%2];" ::"r"(dst),
               "l"(m), "r"(bar), "r"(c0), "r"(c1)
               : "memory");
}
__device__ __forceinline__ void tma2d_mc(uint32_t dst, const CUtensorMap* m, int c0, int c1, uint32_t bar) {
  asm volatile(
      "cp.async.bulk.tensor.2d.shared::cluster.global.mbarrier::complete_tx::bytes.multicast::cluster [%0], [%1, {%3, %4}], [%2], %5;" ::"r"(dst),
      "l"(m), "r"(bar), "r"(c0), "r"(c1), "h"((uint16_t)3)
      : "memory");
}
__device__ __forceinline__ void tma2d_prefetch(const CUtensorMap* m, int c0, int c1) {
  asm volatile("cp.async.bulk.prefetch.tensor.2d.L2.global.tile [%0, {%1, %2}];" ::"l"(m), "r"(c0), "r"(c1) : "memory");
}
__device__ __forceinline__ void bulk_g2s(uint32_t dst, const void* src, uint32_t bytes, uint32_t bar) {
  asm volatile("cp.async.bulk.shared::cluster.global.mbarrier::complete_tx::bytes [%0], [%1], %2, [%3];" ::"r"(dst), "l"(src),
               "r"(bytes), "r"(bar)
               : "memory");
}
__device__ __forceinline__ void wg_fence() { asm volatile("wgmma.fence.sync.aligned;" ::: "memory"); }
__device__ __forceinline__ void wg_commit() { asm volatile("wgmma.commit_group.sync.aligned;" ::: "memory"); }
template <int N>
__device__ __forceinline__ void wg_wait() { asm volatile("wgmma.wait_group.sync.aligned %0;" ::"n"(N) : "memory"); }
template <int N>
__device__ __forceinline__ void pin(float (&d)[N]) {
#pragma unroll
  for (int i = 0; i < N; i++) asm volatile("" : "+f"(d[i])::"memory");
}
__device__ __forceinline__ uint64_t make_desc(uint32_t addr, uint32_t lbo, uint32_t sbo, uint32_t swz) {
  return (uint64_t)((addr & 0x3FFFF) >> 4) | ((uint64_t)(lbo >> 4) << 16) | ((uint64_t)(sbo >> 4) << 32) | ((uint64_t)swz << 62);
}
__device__ __forceinline__ uint32_t pack2(float lo, float hi) {
  uint32_t r;
  asm("cvt.rn.bf16x2.f32 %0, %1, %2;" : "=r"(r) : "f"(hi), "f"(lo));
  return r;
}
__device__ __forceinline__ float bf_lo(uint32_t v) { return __uint_as_float(v << 16); }
__device__ __forceinline__ float bf_hi(uint32_t v) { return __uint_as_float(v & 0xffff0000u); }
__device__ __forceinline__ float bf_round(float v) { return bf_lo(pack2(v, 0.f)); }
__device__ __forceinline__ uint32_t hsub2(uint32_t a, uint32_t b) {
  uint32_t r;
  asm("sub.rn.bf16x2 %0, %1, %2;" : "=r"(r) : "r"(a), "r"(b));
  return r;
}
__device__ __forceinline__ uint32_t hadd2(uint32_t a, uint32_t b) {
  uint32_t r;
  asm("add.rn.bf16x2 %0, %1, %2;" : "=r"(r) : "r"(a), "r"(b));
  return r;
}
__device__ __forceinline__ uint32_t hnorm2(uint32_t d, uint32_t rhi, uint32_t rlo) {
  uint32_t r;
  asm("{\n.reg .b32 t;\nmul.rn.bf16x2 t, %1, %3;\nfma.rn.bf16x2 %0, %1, %2, t;\n}" : "=r"(r) : "r"(d), "r"(rhi), "r"(rlo));
  return r;
}
__device__ __forceinline__ float tanh_ap(float x) {
  float y;
  asm("tanh.approx.f32 %0, %1;" : "=f"(y) : "f"(x));
  return y;
}
__device__ __forceinline__ float ex2_ap(float x) {
  float y;
  asm("ex2.approx.ftz.f32 %0, %1;" : "=f"(y) : "f"(x));
  return y;
}
__device__ __forceinline__ void ldsm4(uint32_t& r0, uint32_t& r1, uint32_t& r2, uint32_t& r3, uint32_t a) {
  asm volatile("ldmatrix.sync.aligned.m8n8.x4.shared.b16 {%0,%1,%2,%3}, [%4];" : "=r"(r0), "=r"(r1), "=r"(r2), "=r"(r3) : "r"(a) : "memory");
}
__device__ __forceinline__ void ldsm2(uint32_t& r0, uint32_t& r1, uint32_t a) {
  asm volatile("ldmatrix.sync.aligned.m8n8.x2.shared.b16 {%0,%1}, [%2];" : "=r"(r0), "=r"(r1) : "r"(a) : "memory");
}
__device__ __forceinline__ void stsm4(uint32_t a, uint32_t r0, uint32_t r1, uint32_t r2, uint32_t r3) {
  asm volatile("stmatrix.sync.aligned.m8n8.x4.shared.b16 [%0], {%1,%2,%3,%4};" ::"r"(a), "r"(r0), "r"(r1), "r"(r2), "r"(r3) : "memory");
}
__device__ __forceinline__ void hmma(float (&c)[4], uint32_t a0, uint32_t a1, uint32_t a2, uint32_t a3, uint32_t b0, uint32_t b1) {
  asm volatile("mma.sync.aligned.m16n8k16.row.col.f32.bf16.bf16.f32 {%0,%1,%2,%3}, {%4,%5,%6,%7}, {%8,%9}, {%0,%1,%2,%3};"
               : "+f"(c[0]), "+f"(c[1]), "+f"(c[2]), "+f"(c[3])
               : "r"(a0), "r"(a1), "r"(a2), "r"(a3), "r"(b0), "r"(b1));
}
__device__ __forceinline__ uint32_t opaque(uint32_t a) { asm volatile("" : "+r"(a)::"memory"); return a; }
__device__ __forceinline__ uint32_t lds16_f(uint32_t a) {
  uint16_t r;
  asm("ld.shared.u16 %0, [%1];" : "=h"(r) : "r"(a));
  return r;
}
__device__ __forceinline__ void sts64(uint32_t a, uint32_t r0, uint32_t r1) {
  asm volatile("st.shared.v2.b32 [%0], {%1,%2};" ::"r"(a), "r"(r0), "r"(r1) : "memory");
}
__device__ __forceinline__ uint32_t vmov(uint32_t a) {
  uint32_t r;
  asm volatile("mov.b32 %0, %1;" : "=r"(r) : "r"(a));
  return r;
}
__device__ __forceinline__ float sqrt_ap(float x) {
  float y;
  asm("sqrt.approx.f32 %0, %1;" : "=f"(y) : "f"(x));
  return y;
}
__device__ __forceinline__ float rcp_ap(float x) {
  float y;
  asm("rcp.approx.f32 %0, %1;" : "=f"(y) : "f"(x));
  return y;
}
__device__ __forceinline__ uint32_t tid_now() {
  uint32_t r;
  asm volatile("mov.u32 %0, %%tid.x;" : "=r"(r));
  return r;
}
__device__ __forceinline__ uint32_t frag_off(uint32_t t) {
  return ((t & 0xe0u) >> 1 | (t & 15u)) * 128 + ((((t >> 4) & 1u) ^ (t & 7u)) << 4);
}
__device__ __forceinline__ uint32_t stat_off(uint32_t t) { return ((t & 0xe0u) >> 1 | (t & 31u) >> 2) * 8; }
__device__ __forceinline__ uint32_t swz(uint32_t a) { return a ^ (((a >> 7) & 3) << 4); }
__device__ __forceinline__ void ldsm4t(uint32_t& r0, uint32_t& r1, uint32_t& r2, uint32_t& r3, uint32_t a) {
  asm volatile("ldmatrix.sync.aligned.m8n8.x4.trans.shared.b16 {%0,%1,%2,%3}, [%4];" : "=r"(r0), "=r"(r1), "=r"(r2), "=r"(r3) : "r"(a) : "memory");
}
__device__ __forceinline__ void lds128(uint32_t& r0, uint32_t& r1, uint32_t& r2, uint32_t& r3, uint32_t a) {
  asm volatile("ld.shared.v4.b32 {%0,%1,%2,%3}, [%4];" : "=r"(r0), "=r"(r1), "=r"(r2), "=r"(r3) : "r"(a) : "memory");
}
__device__ __forceinline__ void sts128(uint32_t a, uint32_t r0, uint32_t r1, uint32_t r2, uint32_t r3) {
  asm volatile("st.shared.v4.b32 [%0], {%1,%2,%3,%4};" ::"r"(a), "r"(r0), "r"(r1), "r"(r2), "r"(r3) : "memory");
}
__device__ __forceinline__ uint32_t lds32(uint32_t a) {
  uint32_t r;
  asm volatile("ld.shared.b32 %0, [%1];" : "=r"(r) : "r"(a) : "memory");
  return r;
}
__device__ __forceinline__ void sts32(uint32_t a, uint32_t v) { asm volatile("st.shared.b32 [%0], %1;" ::"r"(a), "r"(v) : "memory"); }
__device__ __forceinline__ void sts16(uint32_t a, uint32_t v) { asm volatile("st.shared.u16 [%0], %1;" ::"r"(a), "h"((uint16_t)v) : "memory"); }
__device__ __forceinline__ uint4 ldg128_cg(const uint4* p) {
  uint4 v;
  asm volatile("ld.relaxed.gpu.global.v4.u32 {%0,%1,%2,%3}, [%4];" : "=r"(v.x), "=r"(v.y), "=r"(v.z), "=r"(v.w) : "l"(p) : "memory");
  return v;
}
__device__ __forceinline__ void stg128(void* p, uint32_t a, uint32_t b, uint32_t c, uint32_t d) {
  asm volatile("st.global.v4.u32 [%0], {%1,%2,%3,%4};" ::"l"(p), "r"(a), "r"(b), "r"(c), "r"(d) : "memory");
}
__device__ __forceinline__ void stg128_rlx(void* p, uint32_t a, uint32_t b, uint32_t c, uint32_t d) {
  asm volatile("st.relaxed.gpu.global.v4.u32 [%0], {%1,%2,%3,%4};" ::"l"(p), "r"(a), "r"(b), "r"(c), "r"(d) : "memory");
}
__device__ __forceinline__ uint32_t ldg32_cg(const void* p) {
  uint32_t v;
  asm volatile("ld.relaxed.gpu.global.u32 %0, [%1];" : "=r"(v) : "l"(p) : "memory");
  return v;
}

#define TR(slot)
#define TRX(slot)

__device__ __forceinline__ void mma_n128_rs(float (&d)[64], uint32_t a0, uint32_t a1, uint32_t a2, uint32_t a3, uint64_t db, int sd) {
  asm volatile("{\n.reg .pred p;\nsetp.ne.b32 p, %69, 0;\n"
    "wgmma.mma_async.sync.aligned.m64n128k16.f32.bf16.bf16 {%0, %1, %2, %3, %4, %5, %6, %7, %8, %9, %10, %11, %12, %13, %14, %15, %16, %17, %18, %19, %20, %21, %22, %23, %24, %25, %26, %27, %28, %29, %30, %31, %32, %33, %34, %35, %36, %37, %38, %39, %40, %41, %42, %43, %44, %45, %46, %47, %48, %49, %50, %51, %52, %53, %54, %55, %56, %57, %58, %59, %60, %61, %62, %63}, {%64,%65,%66,%67}, %68, p, 1, 1, 1;\n}"
    : "+f"(d[0]), "+f"(d[1]), "+f"(d[2]), "+f"(d[3]), "+f"(d[4]), "+f"(d[5]), "+f"(d[6]), "+f"(d[7]), "+f"(d[8]), "+f"(d[9]), "+f"(d[10]), "+f"(d[11]), "+f"(d[12]), "+f"(d[13]), "+f"(d[14]), "+f"(d[15]), "+f"(d[16]), "+f"(d[17]), "+f"(d[18]), "+f"(d[19]), "+f"(d[20]), "+f"(d[21]), "+f"(d[22]), "+f"(d[23]), "+f"(d[24]), "+f"(d[25]), "+f"(d[26]), "+f"(d[27]), "+f"(d[28]), "+f"(d[29]), "+f"(d[30]), "+f"(d[31]), "+f"(d[32]), "+f"(d[33]), "+f"(d[34]), "+f"(d[35]), "+f"(d[36]), "+f"(d[37]), "+f"(d[38]), "+f"(d[39]), "+f"(d[40]), "+f"(d[41]), "+f"(d[42]), "+f"(d[43]), "+f"(d[44]), "+f"(d[45]), "+f"(d[46]), "+f"(d[47]), "+f"(d[48]), "+f"(d[49]), "+f"(d[50]), "+f"(d[51]), "+f"(d[52]), "+f"(d[53]), "+f"(d[54]), "+f"(d[55]), "+f"(d[56]), "+f"(d[57]), "+f"(d[58]), "+f"(d[59]), "+f"(d[60]), "+f"(d[61]), "+f"(d[62]), "+f"(d[63])
    : "r"(a0), "r"(a1), "r"(a2), "r"(a3), "l"(db), "r"(sd));
}
__device__ __forceinline__ void mma_n128_ss(float (&d)[64], uint64_t da, uint64_t db, int sd) {
  asm volatile("{\n.reg .pred p;\nsetp.ne.b32 p, %66, 0;\n"
    "wgmma.mma_async.sync.aligned.m64n128k16.f32.bf16.bf16 {%0, %1, %2, %3, %4, %5, %6, %7, %8, %9, %10, %11, %12, %13, %14, %15, %16, %17, %18, %19, %20, %21, %22, %23, %24, %25, %26, %27, %28, %29, %30, %31, %32, %33, %34, %35, %36, %37, %38, %39, %40, %41, %42, %43, %44, %45, %46, %47, %48, %49, %50, %51, %52, %53, %54, %55, %56, %57, %58, %59, %60, %61, %62, %63}, %64, %65, p, 1, 1, 0, 1;\n}"
    : "+f"(d[0]), "+f"(d[1]), "+f"(d[2]), "+f"(d[3]), "+f"(d[4]), "+f"(d[5]), "+f"(d[6]), "+f"(d[7]), "+f"(d[8]), "+f"(d[9]), "+f"(d[10]), "+f"(d[11]), "+f"(d[12]), "+f"(d[13]), "+f"(d[14]), "+f"(d[15]), "+f"(d[16]), "+f"(d[17]), "+f"(d[18]), "+f"(d[19]), "+f"(d[20]), "+f"(d[21]), "+f"(d[22]), "+f"(d[23]), "+f"(d[24]), "+f"(d[25]), "+f"(d[26]), "+f"(d[27]), "+f"(d[28]), "+f"(d[29]), "+f"(d[30]), "+f"(d[31]), "+f"(d[32]), "+f"(d[33]), "+f"(d[34]), "+f"(d[35]), "+f"(d[36]), "+f"(d[37]), "+f"(d[38]), "+f"(d[39]), "+f"(d[40]), "+f"(d[41]), "+f"(d[42]), "+f"(d[43]), "+f"(d[44]), "+f"(d[45]), "+f"(d[46]), "+f"(d[47]), "+f"(d[48]), "+f"(d[49]), "+f"(d[50]), "+f"(d[51]), "+f"(d[52]), "+f"(d[53]), "+f"(d[54]), "+f"(d[55]), "+f"(d[56]), "+f"(d[57]), "+f"(d[58]), "+f"(d[59]), "+f"(d[60]), "+f"(d[61]), "+f"(d[62]), "+f"(d[63])
    : "l"(da), "l"(db), "r"(sd));
}
__device__ __forceinline__ void mma_n64_rs(float (&d)[32], uint32_t a0, uint32_t a1, uint32_t a2, uint32_t a3, uint64_t db, int sd) {
  asm volatile("{\n.reg .pred p;\nsetp.ne.b32 p, %37, 0;\n"
    "wgmma.mma_async.sync.aligned.m64n64k16.f32.bf16.bf16 {%0, %1, %2, %3, %4, %5, %6, %7, %8, %9, %10, %11, %12, %13, %14, %15, %16, %17, %18, %19, %20, %21, %22, %23, %24, %25, %26, %27, %28, %29, %30, %31}, {%32,%33,%34,%35}, %36, p, 1, 1, 1;\n}"
    : "+f"(d[0]), "+f"(d[1]), "+f"(d[2]), "+f"(d[3]), "+f"(d[4]), "+f"(d[5]), "+f"(d[6]), "+f"(d[7]), "+f"(d[8]), "+f"(d[9]), "+f"(d[10]), "+f"(d[11]), "+f"(d[12]), "+f"(d[13]), "+f"(d[14]), "+f"(d[15]), "+f"(d[16]), "+f"(d[17]), "+f"(d[18]), "+f"(d[19]), "+f"(d[20]), "+f"(d[21]), "+f"(d[22]), "+f"(d[23]), "+f"(d[24]), "+f"(d[25]), "+f"(d[26]), "+f"(d[27]), "+f"(d[28]), "+f"(d[29]), "+f"(d[30]), "+f"(d[31])
    : "r"(a0), "r"(a1), "r"(a2), "r"(a3), "l"(db), "r"(sd));
}
__device__ __forceinline__ void mma_n64_ss(float (&d)[32], uint64_t da, uint64_t db, int sd) {
  asm volatile("{\n.reg .pred p;\nsetp.ne.b32 p, %34, 0;\n"
    "wgmma.mma_async.sync.aligned.m64n64k16.f32.bf16.bf16 {%0, %1, %2, %3, %4, %5, %6, %7, %8, %9, %10, %11, %12, %13, %14, %15, %16, %17, %18, %19, %20, %21, %22, %23, %24, %25, %26, %27, %28, %29, %30, %31}, %32, %33, p, 1, 1, 0, 1;\n}"
    : "+f"(d[0]), "+f"(d[1]), "+f"(d[2]), "+f"(d[3]), "+f"(d[4]), "+f"(d[5]), "+f"(d[6]), "+f"(d[7]), "+f"(d[8]), "+f"(d[9]), "+f"(d[10]), "+f"(d[11]), "+f"(d[12]), "+f"(d[13]), "+f"(d[14]), "+f"(d[15]), "+f"(d[16]), "+f"(d[17]), "+f"(d[18]), "+f"(d[19]), "+f"(d[20]), "+f"(d[21]), "+f"(d[22]), "+f"(d[23]), "+f"(d[24]), "+f"(d[25]), "+f"(d[26]), "+f"(d[27]), "+f"(d[28]), "+f"(d[29]), "+f"(d[30]), "+f"(d[31])
    : "l"(da), "l"(db), "r"(sd));
}
__device__ __forceinline__ void cmma_rs(float (&d)[32], uint32_t a0, uint32_t a1, uint32_t a2, uint32_t a3, uint64_t db, int sd) {
  asm volatile("{\n.reg .pred p;\nsetp.ne.b32 p, %37, 0;\n"
    "wgmma.mma_async.sync.aligned.m64n64k16.f32.bf16.bf16 {%0, %1, %2, %3, %4, %5, %6, %7, %8, %9, %10, %11, %12, %13, %14, %15, %16, %17, %18, %19, %20, %21, %22, %23, %24, %25, %26, %27, %28, %29, %30, %31}, {%32,%33,%34,%35}, %36, p, 1, 1, 0;\n}"
    : "+f"(d[0]), "+f"(d[1]), "+f"(d[2]), "+f"(d[3]), "+f"(d[4]), "+f"(d[5]), "+f"(d[6]), "+f"(d[7]), "+f"(d[8]), "+f"(d[9]), "+f"(d[10]), "+f"(d[11]), "+f"(d[12]), "+f"(d[13]), "+f"(d[14]), "+f"(d[15]), "+f"(d[16]), "+f"(d[17]), "+f"(d[18]), "+f"(d[19]), "+f"(d[20]), "+f"(d[21]), "+f"(d[22]), "+f"(d[23]), "+f"(d[24]), "+f"(d[25]), "+f"(d[26]), "+f"(d[27]), "+f"(d[28]), "+f"(d[29]), "+f"(d[30]), "+f"(d[31])
    : "r"(a0), "r"(a1), "r"(a2), "r"(a3), "l"(db), "r"(sd));
}
__device__ __forceinline__ void cmma_ss(float (&d)[32], uint64_t da, uint64_t db, int sd) {
  asm volatile("{\n.reg .pred p;\nsetp.ne.b32 p, %34, 0;\n"
    "wgmma.mma_async.sync.aligned.m64n64k16.f32.bf16.bf16 {%0, %1, %2, %3, %4, %5, %6, %7, %8, %9, %10, %11, %12, %13, %14, %15, %16, %17, %18, %19, %20, %21, %22, %23, %24, %25, %26, %27, %28, %29, %30, %31}, %32, %33, p, 1, 1, 0, 0;\n}"
    : "+f"(d[0]), "+f"(d[1]), "+f"(d[2]), "+f"(d[3]), "+f"(d[4]), "+f"(d[5]), "+f"(d[6]), "+f"(d[7]), "+f"(d[8]), "+f"(d[9]), "+f"(d[10]), "+f"(d[11]), "+f"(d[12]), "+f"(d[13]), "+f"(d[14]), "+f"(d[15]), "+f"(d[16]), "+f"(d[17]), "+f"(d[18]), "+f"(d[19]), "+f"(d[20]), "+f"(d[21]), "+f"(d[22]), "+f"(d[23]), "+f"(d[24]), "+f"(d[25]), "+f"(d[26]), "+f"(d[27]), "+f"(d[28]), "+f"(d[29]), "+f"(d[30]), "+f"(d[31])
    : "l"(da), "l"(db), "r"(sd));
}

__device__ __forceinline__ void delay_until(uint32_t t0) {
#pragma unroll 1
  for (int it = 0; it < 1000 && (int)(clock() - t0) < PREDELAY; it++) __nanosleep(100);
}
__device__ __forceinline__ void tag_repair(uint32_t sa, const uint4* g, unsigned par) {
  if (((lds32(sa) ^ par) & 1u) == 0) return;
  uint4 v;
#pragma unroll 1
  for (int it = 0; it < 20000; it++) {
    v = ldg128_cg(g);
    if (((v.x ^ par) & 1u) == 0) break;
  }
  sts128(sa, v.x, v.y, v.z, v.w);
}

#define FEXP(b, n) mbar_expect_tx(b, n)
#define FOP
#define BADCHK(x) (x)
struct Params {
  const __nv_bfloat16 *x, *a_re, *a_im, *b_re, *b_im, *c_re, *c_im, *log_dt, *dskip;
  __nv_bfloat16* out;
};

template <bool B>
struct BoolC {
  static constexpr bool value = B;
};
struct KParams {
  uint2 are, aim, bre, bim, cre, cim;
  __nv_bfloat16 ldt;
};

struct cf {
  float r, i;
};
__device__ __forceinline__ cf cmul(cf a, cf b) { return {fmaf(a.r, b.r, -(a.i * b.i)), fmaf(a.r, b.i, a.i * b.r)}; }
__device__ __forceinline__ cf cmulc(cf a, cf b) { return {fmaf(a.r, b.r, a.i * b.i), fmaf(a.i, b.r, -(a.r * b.i))}; }
__device__ __forceinline__ cf csq(cf a) { return {fmaf(a.r, a.r, -(a.i * a.i)), (a.r + a.r) * a.i}; }
__device__ __forceinline__ cf cexp(float a2, float th, float v) {
  const float mag = ex2_ap(a2 * v), ang = th * v;
  return {mag * __cosf(ang), mag * __sinf(ang)};
}

__device__ __forceinline__ void conv_mma(uint32_t ws, int warp, int lane, int barid) {
  ws = __shfl_sync(0xffffffffu, opaque(ws), 0);
  float y[32];
  uint32_t f[16];
  TR(56);
  {
    const uint32_t sa = (uint32_t)(4 * ((lane & 7) + 8 * (lane >> 4) + 16 * ((lane >> 3) & 1)) + 7 - warp) * 16;
#pragma unroll
    for (int e = 1; e <= 4; e++) ldsm4t(f[4 * e - 4], f[4 * e - 3], f[4 * e - 2], f[4 * e - 1], swz(ws + ((e & 1) ? W_S7 : W_S9) + sa - e * 16));
  }
  const uint64_t da = make_desc(ws + W_A, 288, 144, 0), dx = make_desc(ws + W_X, 16, 512, 2), dh = make_desc(ws + W_H, 128, 128, 0);
  wg_fence();
#pragma unroll
  for (int s = 0; s < 35; s++) cmma_ss(y, da + (uint64_t)((68 - 2 * s) * 18), dx + (uint64_t)((s >> 1) * 4 + (1 - (s & 1)) * 2), s != 0);
  wg_fence();
#pragma unroll
  for (int e = 0; e < 4; e++) cmma_rs(y, f[4 * e], f[4 * e + 1], f[4 * e + 2], f[4 * e + 3], dh + (uint64_t)(e * 72), 1);
  wg_commit();
  bar_sync(barid, 128);
  wg_wait<0>();
  pin(y);
  TR(59);
  uint32_t o[8];
#pragma unroll
  for (int j = 0; j < 8; j++) o[j] = j < 6 ? pack2(y[4 * j] + y[4 * j + 10], y[4 * j + 1] + y[4 * j + 11]) : pack2(y[4 * j], y[4 * j + 1]);
  sts128(ws + W_Y + (warp * 32 + lane) * 16, o[0], o[1], o[2], o[3]);
  sts128(ws + W_Y + 2048 + (warp * 32 + lane) * 16, o[4], o[5], o[6], o[7]);
  TR(60);
}

template <bool LAST16>
__device__ __forceinline__ void conv_store(const uint32_t (&yk)[4][8], int warp, int lane, int grp) {
  constexpr int RG = LAST16 ? 256 : 16;
  uint2* dst = reinterpret_cast<uint2*>(g_y) + (size_t)(31 - (lane & 3)) * 144 * 64 + (LAST16 ? 128 * 64 + (grp - 128) * 16 : grp * 64) +
               ((3 - warp) >> 1) * RG + ((3 - warp) & 1) * 8 + (7 - (lane >> 2));
#pragma unroll
  for (int j = 0; j < 8; j++) {
    dst[-(4 * j) * 144 * 64 + 2 * RG] = make_uint2(__byte_perm(yk[0][j], yk[1][j], 0x5410), __byte_perm(yk[2][j], yk[3][j], 0x5410));
    dst[-(4 * j) * 144 * 64] = make_uint2(__byte_perm(yk[0][j], yk[1][j], 0x7632), __byte_perm(yk[2][j], yk[3][j], 0x7632));
  }
}
__device__ __forceinline__ void conv_out(uint32_t ws, int tid, uint32_t* yk) {
  lds128(yk[0], yk[1], yk[2], yk[3], ws + W_Y + tid * 16);
  lds128(yk[4], yk[5], yk[6], yk[7], ws + W_Y + 2048 + tid * 16);
}

struct HMul {
  uint32_t rr, ii;
};
__device__ __forceinline__ uint32_t hpack(float lo, float hi) {
  uint32_t r;
  asm("cvt.rn.f16x2.f32 %0, %1, %2;" : "=r"(r) : "f"(hi), "f"(lo));
  return r;
}
__device__ __forceinline__ uint32_t hpack(cf a) { return hpack(a.r, a.i); }
__device__ __forceinline__ HMul hmulof(cf w) { return {hpack(w.r, w.r), hpack(-w.i, w.i)}; }
__device__ __forceinline__ uint32_t hcmul(uint32_t p, const HMul& m) {
  uint32_t r;
  asm("{\n.reg .b32 s;\nprmt.b32 s, %1, %1, 0x1032;\nmul.rn.f16x2 s, s, %3;\nfma.rn.f16x2 %0, %1, %2, s;\n}" : "=r"(r) : "r"(p), "r"(m.rr), "r"(m.ii));
  return r;
}
__device__ __forceinline__ void hmma_f16(float (&c)[4], uint32_t a0, uint32_t a1, uint32_t a2, uint32_t a3, uint32_t b0, uint32_t b1) {
  asm volatile("mma.sync.aligned.m16n8k16.row.col.f32.f16.f16.f32 {%0,%1,%2,%3}, {%4,%5,%6,%7}, {%8,%9}, {%0,%1,%2,%3};"
               : "+f"(c[0]), "+f"(c[1]), "+f"(c[2]), "+f"(c[3])
               : "r"(a0), "r"(a1), "r"(a2), "r"(a3), "r"(b0), "r"(b1));
}
__device__ __forceinline__ void kgroup(uint32_t sa, cf v0, cf v1, const HMul& rb, const HMul& rc) {
  const uint32_t p0 = hpack(v0), p1 = hpack(v1), p2 = hcmul(p0, rb), p3 = hcmul(p1, rb);
  const uint32_t p4 = hcmul(p0, rc), p5 = hcmul(p1, rc), p6 = hcmul(p2, rc), p7 = hcmul(p3, rc);
  stsm4(sa, p0, p1, p2, p3);
  stsm4(sa + 4 * TP, p4, p5, p6, p7);
}

__device__ __forceinline__ void kgen(const KParams& kp, const __nv_bfloat16* dskip, uint32_t ws, int warp, int lane) {
  const int g = lane >> 2, c = lane & 3;
  const uint32_t tb = ws + W_T + warp * (56 * TP);
  const uint32_t sa = tb + (lane >> 3) * TP + (lane & 7) * 16;
  const uint32_t la = tb + ((lane & 7) + 8 * ((lane >> 3) & 1)) * TP + (lane >> 4) * 16;
  const uint32_t lb = tb + (16 + (lane & 7) + 8 * (lane >> 4)) * TP + ((lane >> 3) & 1) * 16;
  const float dt = bf_round(expf(__bfloat162float(kp.ldt)));
  float acc[5][4];
#pragma unroll
  for (int t = 0; t < 5; t++)
#pragma unroll
    for (int i = 0; i < 4; i++) acc[t][i] = 0.f;
  TR(44);
  const uint32_t pm = ws + W_KD + warp * KDP + lane * 16;
  float k0 = 0.f, amax = -3.0e38f;
  uint32_t cmax = 0;
#pragma unroll
  for (int i = 0; i < 4; i++) {
    auto pick = [&](const uint2& v) { const uint32_t x = i < 2 ? v.x : v.y; return (i & 1) ? bf_hi(x) : bf_lo(x); };
    const cf cb = cmul({pick(kp.cre), pick(kp.cim)}, {dt * pick(kp.bre), dt * pick(kp.bim)});
    const float ar = dt * pick(kp.are);
    k0 += cb.r;
    cmax = max(cmax, max(__float_as_uint(fabsf(cb.r)), __float_as_uint(fabsf(cb.i))));
    amax = fmaxf(amax, ar);
    sts128(pm + i * 512, __float_as_uint(ar * 1.4426950408889634f), __float_as_uint(dt * pick(kp.aim)), __float_as_uint(cb.r), __float_as_uint(cb.i));
  }
  cmax = min(max(__reduce_max_sync(0xffffffffu, cmax) & 0x7f800000u, 0x01000000u), 0x7e000000u);
  const float unscale = __uint_as_float(cmax + 0x00800000u);
  if (!__any_sync(0xffffffffu, amax * 2048.f > 9.f)) {
    cf w1, w8, w128, cb;
    auto anchors = [&](int b) {
      uint32_t a2, th, cr, ci;
      lds128(a2, th, cr, ci, pm + b * 512);
      const float scale = __uint_as_float(0x7e800000u - cmax);
      cb = {__uint_as_float(cr) * scale, -__uint_as_float(ci) * scale};
      w1 = cexp(__uint_as_float(a2), __uint_as_float(th), 1.f);
      w8 = cexp(__uint_as_float(a2), __uint_as_float(th), 8.f);
      w128 = cexp(__uint_as_float(a2), __uint_as_float(th), 128.f);
    };
    anchors(0);
#pragma unroll 1
    for (int b = 0; b < 4; b++) {
      {
        const cf w16 = csq(w8), w32 = csq(w16), w64 = csq(w32), v1 = cmulc(cb, w8);
        const uint32_t q0 = hpack(cb), q1 = hpack(v1), q2 = hpack(cmulc(cb, w16)), q3 = hpack(cmulc(v1, w16));
        const HMul m32 = hmulof({w32.r, -w32.i}), m64 = hmulof({w64.r, -w64.i});
        const uint32_t q4 = hcmul(q0, m32), q5 = hcmul(q1, m32), q6 = hcmul(q2, m32), q7 = hcmul(q3, m32);
        stsm4(sa, q0, q1, q2, q3);
        stsm4(sa + 4 * TP, q4, q5, q6, q7);
        stsm4(sa + 8 * TP, hcmul(q0, m64), hcmul(q1, m64), hcmul(q2, m64), hcmul(q3, m64));
        stsm4(sa + 12 * TP, hcmul(q4, m64), hcmul(q5, m64), hcmul(q6, m64), hcmul(q7, m64));
      }
      const cf w2 = csq(w1), w4 = csq(w2), w256 = csq(w128), w258 = csq(cmul(w1, w128)), w516 = csq(w258), w1032 = csq(w516);
      const HMul m4 = hmulof(w4), m128 = hmulof(w128), m256 = hmulof(w256);
      {
        const uint32_t q0 = hpack(w1), q1 = hpack(w2), q2 = hpack(cmul(w2, w1)), q3 = hpack(w4);
        const uint32_t q4 = hcmul(q0, m4), q5 = hcmul(q1, m4), q6 = hcmul(q2, m4), q7 = hpack(w8);
        stsm4(sa + 16 * TP, q0, q1, q2, q3);
        stsm4(sa + 20 * TP, q4, q5, q6, q7);
        stsm4(sa + 24 * TP, hcmul(q0, m128), hcmul(q1, m128), hcmul(q2, m128), hcmul(q3, m128));
        stsm4(sa + 28 * TP, hcmul(q4, m128), hcmul(q5, m128), hcmul(q6, m128), hcmul(q7, m128));
      }
      kgroup(sa + 32 * TP, w258, cmul(w258, w2), m4, m128);
      kgroup(sa + 40 * TP, w516, cmul(w516, w4), m128, m256);
      kgroup(sa + 48 * TP, w1032, cmul(w1032, w128), m256, hmulof(csq(w256)));
      __syncwarp();
#pragma unroll
      for (int k2 = 0; k2 < 2; k2++) {
        uint32_t fa[2][4], fb[2][10];
#pragma unroll
        for (int k = 0; k < 2; k++) {
          const int ks = 2 * k2 + k;
          ldsm4(fa[k][0], fa[k][1], fa[k][2], fa[k][3], la + ks * 32);
          ldsm4(fb[k][0], fb[k][1], fb[k][2], fb[k][3], lb + ks * 32);
          ldsm4(fb[k][4], fb[k][5], fb[k][6], fb[k][7], lb + 16 * TP + ks * 32);
          ldsm2(fb[k][8], fb[k][9], lb + 32 * TP + ks * 32);
        }
        if (k2 == 0) anchors((b + 1) & 3);
#pragma unroll
        for (int k = 0; k < 2; k++)
#pragma unroll
          for (int t = 0; t < 5; t++) hmma_f16(acc[t], fa[k][0], fa[k][1], fa[k][2], fa[k][3], fb[k][2 * t], fb[k][2 * t + 1]);
      }
      __syncwarp();
    }
#pragma unroll
    for (int t = 0; t < 5; t++)
#pragma unroll
      for (int i = 0; i < 4; i++) acc[t][i] *= unscale;
  } else {
    __syncwarp();
    {
#pragma unroll 1
      for (int n = 0; n < 128; n++) {
        uint32_t ua, ut, ur, ui;
        lds128(ua, ut, ur, ui, pm - lane * 16 + n * 16);
        const float na = __uint_as_float(ua), nt = __uint_as_float(ut), nr = __uint_as_float(ur), ni = __uint_as_float(ui);
#pragma unroll
        for (int t = 0; t < 5; t++)
#pragma unroll
          for (int i = 0; i < 4; i++) {
            const int col = 2 * c + (i & 1), j = g + 8 * (i >> 1);
            const int o = t == 0 ? 1 + col : (t == 1 ? 129 + col : (t == 2 ? 258 + 2 * (col & 3) + 128 * (col >> 2)
                                                                           : (t == 3 ? 516 + 4 * (col & 1) + 128 * (col >> 1) : 1032 + 128 * col)));
            const cf e = cexp(na, nt, (float)(o + 8 * j));
            acc[t][i] += nr * e.r - ni * e.i;
          }
      }
    }
  }
  __syncwarp();
  TR(45);
#pragma unroll
  for (int s = 16; s > 0; s >>= 1) k0 += __shfl_xor_sync(0xffffffffu, k0, s);
  k0 += __bfloat162float(*dskip);
  const uint32_t kh = ws + W_KD + warp * KDP + 2 * KR_T + 1024;
  const uint32_t kd = kh - 1024 + KDH;
  sts16(kh - 1022 + 2 * lane, 0);
  sts16(kd + 2 + 2 * lane, 0);
  for (int i = lane; i < 43; i += 32) sts16(kh - 2 * (1029 + i), 0);
  for (int i = lane; i < 48; i += 32) sts16(kd - 2 * (512 + i), 0);
  if (lane == 0) sts16(kd, pack2(k0, 0.f));
#pragma unroll
  for (int h = 0; h < 2; h++) {
    const int j = g + 8 * h;
    const bool edge = h == 1 && lane == 31;
    const uint32_t t0 = pack2(acc[0][2 * h], acc[0][2 * h + 1]), t1 = pack2(acc[1][2 * h], acc[1][2 * h + 1]);
    const uint32_t t2 = pack2(acc[2][2 * h], acc[2][2 * h + 1]), t3 = pack2(acc[3][2 * h], acc[3][2 * h + 1]);
    const uint32_t t4 = pack2(acc[4][2 * h], acc[4][2 * h + 1]);
    const uint32_t q0 = kd - 2 * (1 + 2 * c + 8 * j);
    sts16(q0, t0); sts16(q0 - 2, t0 >> 16);
    sts16(q0 - 256, t1); sts16(q0 - 258, t1 >> 16);
    const uint32_t q2 = kd - 2 * (258 + 4 * (c & 1) + 128 * (c >> 1) + 8 * j);
    const uint32_t q2u = edge ? kh - 2 * 510 : q2;
    sts16(q2, t2); sts16(q2 - 2, t2 >> 16); sts16(q2u - 4, t2 >> 16); sts16(q2u - 6, t2 >> 16);
    const uint32_t q3 = kh - 2 * (516 + 128 * c + 8 * j);
    sts16(q3 + 2, t3); sts16(q3, t3); sts16(q3 - 2, t3);
#pragma unroll
    for (int k = 2; k <= 6; k++) sts16(q3 - 2 * k, t3 >> 16);
    const uint32_t q4 = ws + W_KC + warp * 256 + 2 * (32 * c + j);
    sts16(q4, t4); sts16(q4 + 32, t4 >> 16);
    if (edge) {
      sts16(kd - 2 * 257, t1 >> 16); sts16(kh - 2 * 514, t2 >> 16);
      sts16(kh - 2 * 1027, t3 >> 16); sts16(kh - 2 * 1028, t3 >> 16);
    }
  }
}

__device__ __forceinline__ void conv_init(uint32_t ws, int tid, int barid) {
  fence_async_smem();
  bar_sync(barid, 128);
  if (tid < 72) sts128(ws + W_X + 4096 + tid * 16, 0, 0, 0, 0);
  if (tid < 40) {
#pragma unroll
    for (int e = 0; e < 4; e++) sts128(ws + W_H + e * 1152 + 512 + tid * 16, 0, 0, 0, 0);
  }
}

__device__ __forceinline__ void conv_prep(uint32_t ws, int tid, int t, int ch, uint32_t xbar, uint32_t xpar, int barid) {
  ws = opaque(ws);
  tid = opaque(tid);
  if (tid == 0) {
    fence_async_global();
    mbar_expect_tx(xbar, 4096);
    bulk_g2s(ws + W_X, g_xt + (size_t)ch * 256, 4096, xbar);
  }
#pragma unroll 1
  for (int blk = tid; blk < 146; blk += 128) {
    uint32_t q[8];
    const uint32_t src = ws + W_KD + t * KDP + ((blk & 1) ? 0 : KDH) + (blk >> 1) * 16, dst = ws + W_A + blk * 144;
    lds128(q[0], q[1], q[2], q[3], src);
    lds128(q[4], q[5], q[6], q[7], src + 16);
    uint32_t o[7];
#pragma unroll
    for (int i = 0; i < 7; i++) o[i] = __byte_perm(q[i], q[i + 1], 0x5432);
#pragma unroll
    for (int r = 0; r < 4; r++) {
      sts128(dst + 32 * r, q[r], q[r + 1], q[r + 2], q[r + 3]);
      sts128(dst + 32 * r + 16, o[r], o[r + 1], o[r + 2], o[r + 3]);
    }
  }
  TR(40);
  {
    const int e = (tid >> 5) + 1, tt = tid & 31;
    const uint32_t kc = ws + W_KC + t * 256 + 2 * (123 + e - 4 * tt);
    uint32_t v[8];
#pragma unroll
    for (int s = 0; s < 8; s++) v[s] = (tt + s <= 31) ? lds16_f(kc - 8 * s) : 0u;
    sts128(ws + W_H + (e - 1) * 1152 + tt * 16, v[0] | (v[1] << 16), v[2] | (v[3] << 16), v[4] | (v[5] << 16), v[6] | (v[7] << 16));
  }
  TR(42);
  mbar_wait(xbar, xpar);
  TR(43);
  bar_sync(barid, 128);
  {
    float xv[16];
    uint32_t w[12];
#pragma unroll
    for (int k = 0; k < 3; k++) {
      const int n = tid + 2 + k;
      lds128(w[4 * k], w[4 * k + 1], w[4 * k + 2], w[4 * k + 3], swz(ws + W_X + (64 - (n >> 2)) * 64 + (n & 3) * 16));
    }
#pragma unroll
    for (int i = 0; i < 8; i++) {
      xv[2 * i] = bf_lo(w[2 + i]);
      xv[2 * i + 1] = bf_hi(w[2 + i]);
    }
    float s7[8], s9[8];
    s7[0] = ((xv[1] + xv[2]) + (xv[3] + xv[4])) + ((xv[5] + xv[6]) + xv[7]);
#pragma unroll
    for (int i = 1; i < 8; i++) s7[i] = s7[i - 1] + (xv[i + 7] - xv[i]);
#pragma unroll
    for (int i = 0; i < 8; i++) s9[i] = s7[i] + (xv[i] + xv[i + 8]);
    sts128(swz(ws + W_S7 + (tid + 3) * 16), pack2(s7[7], s7[6]), pack2(s7[5], s7[4]), pack2(s7[3], s7[2]), pack2(s7[1], s7[0]));
    sts128(swz(ws + W_S9 + (tid + 3) * 16), pack2(s9[7], s9[6]), pack2(s9[5], s9[4]), pack2(s9[3], s9[2]), pack2(s9[1], s9[0]));
    if (tid < 6) sts128(swz(ws + (tid < 3 ? W_S7 + tid * 16 : W_S9 + (tid - 3) * 16)), 0, 0, 0, 0);
  }
  fence_async_smem();
}

template <int U>
__device__ __forceinline__ void export_rows(uint32_t sb, int mt, int sl, uint32_t stg, int lane) {
  const uint32_t bars = sb + OFF_BAR;
  uint32_t done = 0;
#pragma unroll 1
  for (;;) {
    uint32_t u = 0;
    if (lane == 0) asm volatile("atom.shared.add.u32 %0, [%1], 1;" : "=r"(u) : "r"(bars + B_EPOCH + 16) : "memory");
    u = __shfl_sync(0xffffffffu, u, 0);
    if (u >= 9) break;
    const int rg = u < 8 ? u : sl;
    uint32_t rha, rla, rhb, rlb;
    {
      const uint32_t sa = sb + OFF_STAT + (rg * 16 + 2 * (lane & 3)) * 8 + 4;
      const float r0 = __uint_as_float(lds32(sa)), r1 = __uint_as_float(lds32(sa + 8));
      rha = pack2(r0, r1);
      rla = pack2(r0 - bf_lo(rha), r1 - bf_hi(rha));
      const float r2 = __uint_as_float(lds32(sa + 64)), r3 = __uint_as_float(lds32(sa + 72));
      rhb = pack2(r2, r3);
      rlb = pack2(r2 - bf_lo(rhb), r3 - bf_hi(rhb));
    }
    const int rho = 63 - 4 * mt - (rg >> 1);
    uint4* dst = g_xt + (size_t)((u < 8 ? sl * 64 : 512) + (lane >> 1)) * 256 + rho * 4 + ((2 * (rg & 1) + (lane & 1)) ^ ((rho >> 1) & 3));
    const uint32_t src = sb + OFF_XS + (u < 8 ? 0 : 16384) + frag_off(rg * 32 + lane);
#pragma unroll 1
    for (int ks = 0; ks < 4; ks += U) {
      uint32_t x[U][4];
#pragma unroll
      for (int k = 0; k < U; k++) ldsm4t(x[k][0], x[k][1], x[k][2], x[k][3], src ^ ((ks + k) << 5));
      __syncwarp();
#pragma unroll
      for (int k = 0; k < U; k++)
        stsm4(stg + k * 512 + ((lane & 7) + 8 * (lane >> 4)) * 32 + ((lane >> 3) & 1) * 16, hnorm2(x[k][0], rha, rla), hnorm2(x[k][1], rhb, rlb),
              hnorm2(x[k][2], rha, rla), hnorm2(x[k][3], rhb, rlb));
      __syncwarp();
#pragma unroll
      for (int k = 0; k < U; k++) {
        lds128(x[k][0], x[k][1], x[k][2], x[k][3], stg + k * 512 + lane * 16);
        stg128(dst + (ks + k) * 4096, x[k][0], x[k][1], x[k][2], x[k][3]);
      }
    }
    done++;
  }
  if (done) {
    fence_gpu();
    __syncwarp();
    if (lane == 0) asm volatile("mbarrier.arrive.shared::cta.b64 _, [%0], %1;" ::"r"(bars + B_EXP), "r"(done) : "memory");
  }
}

__device__ __forceinline__ int kblock(int pos, int sl) { return pos == 0 ? sl : (pos == 1 ? 8 : (pos - 2 < sl ? pos - 2 : pos - 1)); }

__device__ __forceinline__ void weight_box(int u, int half, int sl, int& which, int& c0, int& c1) {
  const int pass = u / 9, pos = u - pass * 9;
  if (pass < 9) {
    which = half;
    c0 = sl * 576 + pass * 64;
    c1 = kblock(pos, sl) * 64;
  } else {
    const int kc = pos <= 1 ? 8 - pos : pos - 2;
    const int pp = pass - 9;
    const int blk = pp == 4 ? sl : ((pp == 0 && half == 0) ? 8 : ((sl + 2 * pp + half) & 7));
    which = 2;
    c0 = blk * 64;
    c1 = sl * 576 + kc * 64;
  }
}

__global__ void __launch_bounds__(512, 1)
    fused_kernel(const __grid_constant__ CUtensorMap map_w1, const __grid_constant__ CUtensorMap map_w3,
                 const __grid_constant__ CUtensorMap map_w2, const __grid_constant__ CUtensorMap map_x, const Params p) {
  extern __shared__ __align__(1024) uint8_t smem_raw[];
  const uint32_t sb = (smem_u32(smem_raw) + 1023) & ~1023u;
  const uint32_t bars = sb + OFF_BAR;
  const int wg = __shfl_sync(0xffffffffu, threadIdx.x >> 7, 0);
  const int warp = __shfl_sync(0xffffffffu, (threadIdx.x >> 5) & 3, 0);
  const int bid = blockIdx.x;
  const bool spare = bid >= 128;
  const int rank = bid & 1, pair = bid >> 1;
  const int mt = 2 * (pair & 7) + rank, sl = (pair >> 3) & 7;

  TR(0);
  KParams kp;
  if (wg == 1 || spare) {
    const int ch = (spare ? 128 + (bid - 128) * 4 + wg : bid) * 4 + warp;
    const size_t o = (size_t)ch * NM_ + (threadIdx.x & 31) * 4;
    kp.are = __ldg(reinterpret_cast<const uint2*>(p.a_re + o)); kp.aim = __ldg(reinterpret_cast<const uint2*>(p.a_im + o));
    kp.bre = __ldg(reinterpret_cast<const uint2*>(p.b_re + o)); kp.bim = __ldg(reinterpret_cast<const uint2*>(p.b_im + o));
    kp.cre = __ldg(reinterpret_cast<const uint2*>(p.c_re + o)); kp.cim = __ldg(reinterpret_cast<const uint2*>(p.c_im + o));
    kp.ldt = p.log_dt[ch];
  }
  if (threadIdx.x == 0 && !spare) {
    asm volatile("prefetch.tensormap [%0];" ::"l"(&map_x) : "memory");
#pragma unroll
    for (int i = 0; i < 9; i++) mbar_init(bars + B_XFULL + 8 * i, 1);
    fence_async_smem();
#pragma unroll
    for (int i = 0; i < 9; i++) {
      const int b = (i + 2) % 9;
      tma2d(sb + (b <= 1 ? OFF_XS + b * 16384 : b * STAGE), &map_x, kblock(b, sl) * 64, mt * 128, bars + B_XFULL + 8 * b);
      mbar_expect_tx(bars + B_XFULL + 8 * b, 16384);
    }
    asm volatile("prefetch.tensormap [%0];" ::"l"(&map_w1) : "memory");
    asm volatile("prefetch.tensormap [%0];" ::"l"(&map_w3) : "memory");
    asm volatile("prefetch.tensormap [%0];" ::"l"(&map_w2) : "memory");
  }
  if (threadIdx.x == 32) {
    for (int i = 0; i < NST; i++) {
      mbar_init(bars + B_FULL + 8 * i, 1);
      mbar_init(bars + B_EMPTY + 8 * i, 4);
    }
    for (int i = 0; i < 2; i++) mbar_init(bars + B_PASS + 8 * i, 2);
    mbar_init(bars + B_XFREE, 16);
    mbar_init(bars + B_EXP, 9);
    mbar_init(bars + B_HPK, 1);
    mbar_init(bars + B_HFR, 256);
    sts32(bars + B_EPOCH + 16, 0);
    for (int i = 0; i < 4; i++) mbar_init(bars + B_FET + 8 * i, 1);
    for (int i = 0; i < 4; i++) mbar_init(bars + B_FREE + 8 * i, 128);
    mbar_init(bars + B_STATS, 9);
    mbar_init(bars + B_PRESUM, 128);
    mbar_init(bars + B_LAG, 1);
    for (int i = 0; i < 4; i++) {
      mbar_init(bars + B_XCH + 8 * i, 1);
      mbar_init(bars + B_CREADY + 8 * i, 128);
      mbar_init(bars + B_CDONE + 8 * i, 128);
    }
    asm volatile("fence.mbarrier_init.release.cluster;" ::: "memory");
    fence_async_smem();
  }
  __syncthreads();
  asm volatile("barrier.cluster.arrive.relaxed.aligned;\nbarrier.cluster.wait.aligned;" ::: "memory");
#define ep lds32(bars + B_EPOCH)
  TR(1);

  if (wg == 0 && !spare) {
    asm volatile("setmaxnreg.dec.sync.aligned.u32 24;");
    const int lane = tid_now() & 31;
    if (warp == 0) {
      if (lane == 0) {
        uint32_t slot = 0, ph = 1;
        const CUtensorMap* m = rank == 0 ? &map_w1 : &map_w3;
#pragma unroll 1
        for (int pass = 0; pass < 14; pass++) {
          int c0, c1b;
          if (pass < 9) {
            c0 = sl * 576 + pass * 64;
            c1b = 0;
          } else {
            const int pp = pass - 9;
            c0 = 64 * (pp == 4 ? sl : ((pp == 0 && rank == 0) ? 8 : ((sl + 2 * pp + rank) & 7)));
            c1b = sl * 576;
            m = &map_w2;
          }
          const bool last = pass == 13;
          const uint32_t dst0 = sb + rank * 8192;
#pragma unroll 1
          for (int pos = 0; pos < (last ? 5 : 9); pos++) {
            const int kp = last ? 2 * pos + rank : pos;
            const int c1 = c1b + 64 * (pass < 9 ? kblock(kp, sl) : (kp <= 1 ? 8 - kp : kp - 2));
            const uint32_t dst = dst0 + slot * (STAGE / 8), fb = bars + B_FULL + slot;
            if (pass * 9 + pos < NST) {
              if (pos == 2) mbar_wait(bars + B_XFREE, 0);
            } else {
              mbar_wait(bars + B_EMPTY + slot, ph);
            }
            if (kp < 9) tma2d_mc(dst, m, c0, c1, fb);
            mbar_expect_tx(fb, (last && pos == 4) ? 8192 : 16384);
            slot += 8;
            if (slot == 8 * NST) { slot = 0; ph ^= 1; }
          }
        }
        asm volatile("barrier.cluster.arrive.relaxed;\nbarrier.cluster.wait;" ::: "memory");
      }
    } else {
      {
        if (warp == 3 && lane == 0) {
          sts32(bars + B_EPOCH, ldg32_cg(&g_epoch) + 1u);
          mbar_arrive(bars + B_STATS);
        }
      }
      auto prefetch = [&](int u0, int u1) {
#pragma unroll 1
        for (int u = u0 + ((pair - u0) & 7); u < u1; u += 8) {
          if (u >= PFD) mbar_wait_short(bars + B_FULL + 8 * ((u - PFD) % NST), ((u - PFD) / NST) & 1);
          int which, c0, c1;
          weight_box(u, rank, sl, which, c0, c1);
          tma2d_prefetch(which == 0 ? &map_w1 : (which == 1 ? &map_w3 : &map_w2), c0, c1);
        }
      };
      if (warp == 2 && lane == 0) prefetch(2, PFD + 2);
      __syncwarp();
      {
        mbar_wait(bars + B_STATS, 0);
        TRX(4);
        export_rows<1>(sb, mt, sl, sb + OFF_W + W_SIZE + (warp - 1) * 512, lane);
        TRX(5);
        if (warp == 1) {
          mbar_wait(bars + B_EXP, 0);
          if (lane < 2) flag_set(&g_fx[bid], ep, lane);
        }
      }
      if (warp == 2 && lane == 0) prefetch(PFD + 2, 126);
      if (warp == 3) {
        const uint32_t b0 = sb + OFF_B0, b1 = sb + OFF_B1;
        const uint4* inbox = g_part + (size_t)(mt * 9 + sl) * 8 * 1024;
        mbar_wait(bars + B_FREE, 0);
        fence_async_global();
        if (lane == 0) {
          mbar_expect_tx(bars + B_HPK, 32768);
          bulk_g2s(b0, g_hpark + (size_t)bid * (7 * 4 * 256), 32768, bars + B_HPK);
        }
        mbar_wait(bars + B_HFR, 0);
        flag_wait(lane < 16 ? &g_fy[128 + lane] : &g_fy[sl * 16 + lane - 16], ep);
        fence_gpu();
        __syncwarp();
        fence_async_global();
        if (lane == 0) {
          FEXP(bars + B_FET, 16384 + 2048);
          FOP bulk_g2s(b1, g_y + ((size_t)(2 * mt) * 144 + sl * 16) * 32, 8192, bars + B_FET);
          FOP bulk_g2s(b1 + 8192, g_y + ((size_t)(2 * mt + 1) * 144 + sl * 16) * 32, 8192, bars + B_FET);
          FOP bulk_g2s(b0, g_y + ((size_t)(2 * mt + (sl >> 2)) * 144 + 128) * 32 + (sl & 3) * 128, 2048, bars + B_FET);
          TRX(8);
          mbar_wait(bars + B_PASS, 0);
          delay_until(lds32(bars + B_EPOCH + 4));
          mbar_wait(bars + B_FREE + 8, 0);
          FEXP(bars + B_FET + 8, 32768);
          FOP bulk_g2s(b0, g_part + (size_t)((mt * 9 + 8) * 8 + sl) * 1024, 16384, bars + B_FET + 8);
          FOP bulk_g2s(b1, inbox + ((sl - 1) & 7) * 1024, 16384, bars + B_FET + 8);
          TRX(9);
          mbar_wait(bars + B_PASS + 8, 0);
          delay_until(lds32(bars + B_EPOCH + 8));
#pragma unroll 1
          for (int k = 0; k < 2; k++) {
            mbar_wait(bars + B_FREE + 16 + 8 * k, 0);
            FEXP(bars + B_FET + 16 + 8 * k, 16384);
            FOP bulk_g2s(b0, inbox + ((sl - 2 - k) & 7) * 1024, 16384, bars + B_FET + 16 + 8 * k);
          }
          TRX(22);
        }
      }
    }
  } else if (spare) {
    const int tid = tid_now() & 127, lane = tid & 31;
    const uint32_t ws = sb + wg * W_STRIDE;
    const int grp = 128 + (bid - 128) * 4 + wg;
    unsigned ep0 = 0;
    if (warp == 0) ep0 = ldg32_cg(&g_epoch) + 1u;
    kgen(kp, p.dskip + grp * 4 + warp, ws, warp, lane);
    TR(2);
    conv_init(ws, tid, wg + 1);
    if (warp == 0) {
#pragma unroll 1
      for (int k = 0; k < 4; k++) flag_wait(&g_fx[k * 32 + lane], ep0);
      fence_gpu();
      __syncwarp();
    }
    bar_sync(wg + 1, 128);
    TR(3);
    uint32_t yk[4][8];
#pragma unroll 1
    for (int t = 0; t < 4; t++) {
      TR(4 + 2 * t);
      conv_prep(ws, tid, t, grp * 4 + t, bars + B_XCH + 8 * wg, t & 1, wg + 1);
      TR(5 + 2 * t);
      bar_sync(wg + 1, 128);
      conv_mma(ws, warp, lane, wg + 1);
      bar_sync(wg + 1, 128);
      conv_out(ws, tid, yk[t]);
    }
    conv_store<true>(yk, warp, lane, grp);
    fence_gpu();
    bar_sync(wg + 1, 128);
    TR(12);
    if (tid < 2) flag_set(&g_fy[grp], ep0, tid);
  } else if (wg == 1) {
    asm volatile("setmaxnreg.dec.sync.aligned.u32 72;");
    const int tid = tid_now() & 127, lane = tid & 31;
    const int g = lane >> 2, c = lane & 3;
    const uint32_t ws = sb + OFF_W;
    kgen(kp, p.dskip + bid * 4 + warp, ws, warp, lane);
    mbar_wait(bars + B_STATS, 0);
    TR(2);
    export_rows<4>(sb, mt, sl, ws + W_T + warp * (56 * TP), lane);
    conv_init(ws, tid, 2);
    uint32_t x8[4];
    {
      ldsm4(x8[0], x8[1], x8[2], x8[3], sb + OFF_XS + 16384 + (frag_off(sl * 32 + lane) ^ (warp << 5)));
      const float ma = __uint_as_float(lds32(sb + OFF_STAT + (sl * 16 + g) * 8)), mb = __uint_as_float(lds32(sb + OFF_STAT + (sl * 16 + g) * 8 + 64));
      const uint32_t m2a = pack2(ma, ma), m2b = pack2(mb, mb);
      x8[0] = hadd2(x8[0], m2a); x8[1] = hadd2(x8[1], m2b); x8[2] = hadd2(x8[2], m2a); x8[3] = hadd2(x8[3], m2b);
    }
    if (warp == 0) {
      mbar_wait(bars + B_EXP, 0);
#pragma unroll 1
      for (int k = 0; k < 4; k++) flag_wait(&g_fx[k * 32 + lane], ep);
      fence_gpu();
      __syncwarp();
    }
    bar_sync(2, 128);
    TR(3);
    uint32_t yk[4][8];
#pragma unroll 1
    for (int t = 0; t < 4; t++) {
      TR(4 + 2 * t);
      conv_prep(ws, tid, t, bid * 4 + t, bars + B_XCH + 8, t & 1, 2);
      TR(5 + 2 * t);
      mbar_arrive(bars + B_CREADY + 8 * t);
      mbar_wait(bars + B_CDONE + 8 * t, 0);
      conv_out(ws, tid, yk[t]);
    }
    mbar_arrive(bars + B_FREE);
    conv_store<false>(yk, warp, lane, bid);
    fence_gpu();
    bar_sync(2, 128);
    TR(12);
    if (tid < 2) flag_set(&g_fy[bid], ep, tid);
    {
      const uint32_t lm = frag_off(tid);
      const unsigned par = ep & 1u;
      const uint4* inbox = g_part + (size_t)(mt * 9 + sl) * 8 * 1024 + tid;
      mbar_wait(bars + B_FET, 0);
      TR(13);
#pragma unroll 1
      for (int w = 0; w < 2; w++) {
        const uint32_t sa = sb + OFF_STAT + (w * 64 + warp * 16 + g) * 8;
        const float ma = __uint_as_float(lds32(sa)), mb = __uint_as_float(lds32(sa + 64));
        const uint32_t m2a = pack2(ma, ma), m2b = pack2(mb, mb);
        uint32_t x[4][4];
#pragma unroll
        for (int q = 0; q < 4; q++) {
          ldsm4(x[q][0], x[q][1], x[q][2], x[q][3], sb + OFF_XS + w * 8192 + (lm ^ (q << 5)));
          const uint32_t ya = sb + OFF_B1 + w * 8192 + (4 * q + (c >> 1)) * 512 + warp * 128 + g * 8 + (c & 1) * 4;
          x[q][0] = hadd2(hadd2(x[q][0], m2a), lds32(ya));
          x[q][1] = hadd2(hadd2(x[q][1], m2b), lds32(ya + 64));
          x[q][2] = hadd2(hadd2(x[q][2], m2a), lds32(ya + 1024));
          x[q][3] = hadd2(hadd2(x[q][3], m2b), lds32(ya + 1024 + 64));
        }
        __syncwarp();
#pragma unroll
        for (int q = 0; q < 4; q++) sts128(sb + OFF_XS + w * 8192 + warp * 2048 + q * 512 + lane * 16, x[q][0], x[q][1], x[q][2], x[q][3]);
      }
#pragma unroll
      for (int i = 0; i < 4; i++)
        x8[i] = hadd2(x8[i], lds32(sb + OFF_B0 + (2 * (2 * warp + (i >> 1)) + (c >> 1)) * 128 + (i & 1) * 64 + g * 8 + (c & 1) * 4));
      mbar_arrive(bars + B_FREE + 8);
      TR(14);
      mbar_wait(bars + B_FET + 8, 0);
      {
        const float ra = __uint_as_float(lds32(sb + OFF_STAT + (sl * 16 + g) * 8 + 4)), rb = __uint_as_float(lds32(sb + OFF_STAT + (sl * 16 + g) * 8 + 68));
        float s[8];
#pragma unroll
        for (int i = 0; i < 8; i++) s[i] = 0.f;
#pragma unroll 1
        for (int h = 0; h < 2; h++) {
          uint32_t v[4][4], bad = 0;
          const uint32_t sa = sb + OFF_B0 + h * 8192 + tid * 16;
#pragma unroll
          for (int k = 0; k < 4; k++) {
            lds128(v[k][0], v[k][1], v[k][2], v[k][3], sa + k * 2048);
            bad |= v[k][0] ^ par;
          }
          if (BADCHK(bad & 1u)) {
#pragma unroll 1
            for (int k = 0; k < 4; k++)
              tag_repair(sa + k * 2048, g_part + (size_t)((mt * 9 + 8) * 8 + sl) * 1024 + (4 * h + k) * 128 + tid, par);
#pragma unroll
            for (int k = 0; k < 4; k++) lds128(v[k][0], v[k][1], v[k][2], v[k][3], sa + k * 2048);
          }
#pragma unroll
          for (int i = 0; i < 4; i++) {
            s[2 * i] += (bf_lo(v[0][i]) + bf_lo(v[1][i])) + (bf_lo(v[2][i]) + bf_lo(v[3][i]));
            s[2 * i + 1] += (bf_hi(v[0][i]) + bf_hi(v[1][i])) + (bf_hi(v[2][i]) + bf_hi(v[3][i]));
          }
        }
        const uint32_t sg = sb + OFF_B0 + warp * 512;
        uint32_t o0 = pack2(fmaf(ra, s[0], bf_lo(x8[0])), fmaf(ra, s[1], bf_hi(x8[0]))), o1 = pack2(fmaf(rb, s[2], bf_lo(x8[1])), fmaf(rb, s[3], bf_hi(x8[1])));
        uint32_t o2 = pack2(fmaf(ra, s[4], bf_lo(x8[2])), fmaf(ra, s[5], bf_hi(x8[2]))), o3 = pack2(fmaf(rb, s[6], bf_lo(x8[3])), fmaf(rb, s[7], bf_hi(x8[3])));
        __syncwarp();
        stsm4(sg + (lane & 15) * 32 + (lane >> 4) * 16, o0, o1, o2, o3);
        __syncwarp();
        lds128(o0, o1, o2, o3, sg + lane * 16);
        fence_async_smem();
        mbar_arrive(bars + B_FREE + 16);
        stg128(p.out + (size_t)(mt * 128 + sl * 16 + (lane >> 1)) * D_ + 512 + warp * 16 + (lane & 1) * 8, o0, o1, o2, o3);
      }
      TR(15);
#pragma unroll 1
      for (int n = 0; n < 2; n++) {
        mbar_wait(bars + B_FET + 16 + 8 * n, 0);
        TR(16 + n);
#pragma unroll 1
        for (int k = 0; k < 8; k += 4) {
          const uint32_t pa = sb + OFF_B0 + k * 2048 + tid * 16;
          uint32_t u[4][4], v[4][4], bad = 0;
          auto fetch = [&]() {
#pragma unroll
            for (int e = 0; e < 4; e++) {
              lds128(u[e][0], u[e][1], u[e][2], u[e][3], pa + e * 2048);
              lds128(v[e][0], v[e][1], v[e][2], v[e][3], pa + 16384 + e * 2048);
            }
          };
          fetch();
#pragma unroll
          for (int e = 0; e < 4; e++) bad |= (u[e][0] ^ par) | (n == 0 ? v[e][0] ^ par : 0u);
          if (BADCHK(bad & 1u)) {
#pragma unroll 1
            for (int e = 0; e < (n == 0 ? 8 : 4); e++)
              tag_repair(pa + (e >> 2) * 16384 + (e & 3) * 2048, inbox + ((sl - (e >= 4 ? 1 : 2 + n)) & 7) * 1024 + (k + (e & 3)) * 128, par);
            fetch();
          }
#pragma unroll
          for (int e = 0; e < 4; e++)
            sts128(pa + 16384 + e * 2048, hadd2(u[e][0], v[e][0]), hadd2(u[e][1], v[e][1]), hadd2(u[e][2], v[e][2]), hadd2(u[e][3], v[e][3]));
        }
        if (n == 0) {
          fence_async_smem();
          mbar_arrive(bars + B_FREE + 24);
        }
      }
      mbar_arrive(bars + B_PRESUM);
      TR(18);
      if (bid == 0 && tid == 0) *(volatile unsigned*)&g_epoch = ep;
    }
  } else {
    asm volatile("setmaxnreg.inc.sync.aligned.u32 208;");
    const int w = wg - 2;
    uint32_t a[112];
    {
      uint32_t t[32];
      const uint32_t tl = tid_now(), lm = frag_off(tl);
      const int lane = tl & 31;
      float s0[4] = {0.f, 0.f, 0.f, 0.f}, qa[4] = {0.f, 0.f, 0.f, 0.f}, qb[4] = {0.f, 0.f, 0.f, 0.f};
      const uint32_t ONE = 0x3f803f80u;
#pragma unroll
      for (int i = 0; i <= 9; i++) {
        if (i < 9) {
          const int b = (i + 2) % 9;
          mbar_wait(bars + B_XFULL + 8 * b, 0);
          const uint32_t src = sb + (b <= 1 ? OFF_XS + b * 16384 : b * STAGE);
#pragma unroll
          for (int kk = 0; kk < 4; kk++) {
            uint32_t* r = b <= 1 ? &t[16 * b + 4 * kk] : &a[16 * (b - 2) + 4 * kk];
            ldsm4(r[0], r[1], r[2], r[3], src + (lm ^ (kk << 5)));
          }
        }
        if (i == XFI + 1) {
          __syncwarp();
          if (lane < 2) mbar_arrive_cl(mapa(bars + B_XFREE, lane));
        }
        if (i > 0) {
          const int b = (i + 1) % 9;
#pragma unroll
          for (int kk = 0; kk < 4; kk++) {
            uint32_t* r = b <= 1 ? &t[16 * b + 4 * kk] : &a[16 * (b - 2) + 4 * kk];
            hmma(s0, r[0], r[1], r[2], r[3], ONE, ONE);
            hmma(qa, r[0], r[1], r[2], r[3], vmov(r[0]), vmov(r[2]));
            hmma(qb, r[0], r[1], r[2], r[3], vmov(r[1]), vmov(r[3]));
          }
        }
      }
      TR(2);
      const float meana = s0[0] * (1.f / D_), meanb = s0[2] * (1.f / D_);
      const float mba = bf_round(meana), mbb = bf_round(meanb);
      const uint32_t m2a = pack2(mba, mba), m2b = pack2(mbb, mbb);
#pragma unroll
      for (int ks = 0; ks < 8; ks++) {
        uint32_t* r = &t[4 * ks];
        stsm4(sb + OFF_XS + (ks >> 2) * 16384 + (lm ^ ((ks & 3) << 5)), hsub2(r[0], m2a), hsub2(r[1], m2b), hsub2(r[2], m2a), hsub2(r[3], m2b));
      }
      fence_async_smem();
      {
        const int g = lane >> 2;
        const uint32_t sa = sb + OFF_STAT + stat_off(tl);
        if ((lane & 3) == (g >> 1)) {
          sts64(sa, __float_as_uint(mba), __float_as_uint(fmaxf(fmaf(-meana, meana, ((g & 1) ? qa[1] : qa[0]) * (1.f / D_)), 0.f)));
          sts64(sa + 64, __float_as_uint(mbb), __float_as_uint(fmaxf(fmaf(-meanb, meanb, ((g & 1) ? qb[3] : qb[2]) * (1.f / D_)), 0.f)));
        }
      }
      TR(49);
      bar_sync(6 + w, 128);
    }
    const bool rel = (tid_now() & 0x5f) == 0;
    const uint32_t ebar = mapa(bars + B_EMPTY, warp & 1);
    const uint64_t dB = make_desc(sb, 8192, 1024, 1);
    uint32_t ph = 0, lagp = 0;
    bool lead = w == 0;
    auto finish_stats = [&]() {
      const uint32_t t = tid_now();
      {
        const float ma = __uint_as_float(lds32(sb + OFF_STAT + stat_off(t))), mb = __uint_as_float(lds32(sb + OFF_STAT + stat_off(t) + 64));
        const uint32_t m2a = pack2(ma, ma), m2b = pack2(mb, mb);
#pragma unroll
        for (int i = 0; i < 112; i++) a[i] = hsub2(a[i], (i & 1) ? m2b : m2a);
      }
      if ((t & 31) < 16) {
        const uint32_t sa = sb + OFF_STAT + (((t & 0xe0u) >> 1) + (t & 15)) * 8 + 4;
        sts32(sa, __float_as_uint(rcp_ap(bf_round(sqrt_ap(bf_round(bf_round(__uint_as_float(lds32(sa))) + 1e-5f))))));
      }
      __syncwarp();
      if ((t & 31) == 0) mbar_arrive(bars + B_STATS);
    };
    float rha, rhb;
    auto tile128 = [&](float (&acc)[64], const uint64_t dA, const bool first, auto reload, auto gemm1) {
      if (!lead) {
        if (first) finish_stats();
        mbar_wait(bars + B_LAG, lagp);
      }
      lagp ^= 1;
      mbar_wait(bars + B_FULL, ph);
#pragma unroll
      for (int pos = 0; pos < 9; pos++) {
        const uint64_t d = dB + (uint64_t)(pos * (STAGE >> 4));
        wg_fence();
#pragma unroll
        for (int kk = 0; kk < 4; kk++) {
          if (pos <= 1) mma_n128_ss(acc, dA + (uint64_t)(pos * 1024 + kk * 2), d + kk * 128, (pos | kk) != 0);
          else {
            const int o = 16 * (pos - 2) + 4 * kk;
            mma_n128_rs(acc, a[o], a[o + 1], a[o + 2], a[o + 3], d + kk * 128, 1);
          }
        }
        wg_commit();
        if (pos == FSPOS && first && lead) finish_stats();
        if (decltype(reload)::value && pos == 0) {
          mbar_wait(bars + B_HPK, 0);
          const uint32_t src = sb + OFF_B0 + (tid_now() - 256) * 16;
#pragma unroll
          for (int q = 0; q < 8; q++) lds128(a[4 * q], a[4 * q + 1], a[4 * q + 2], a[4 * q + 3], src + q * 4096);
        }
        if (decltype(reload)::value && pos == 2) mbar_arrive(bars + B_HFR);
        if (decltype(reload)::value && pos >= RL0 && pos < RL0 + 2) {
          const uint4* park = g_hpark + (size_t)bid * (7 * 4 * 256) + (tid_now() - 256);
#pragma unroll
          for (int q = 8 + 10 * (pos - RL0); q < 18 + 10 * (pos - RL0); q++) {
            const uint4 v = park[q * 256];
            a[4 * q] = v.x; a[4 * q + 1] = v.y; a[4 * q + 2] = v.z; a[4 * q + 3] = v.w;
          }
        }
        if (pos == LAGPOS && lead && (tid_now() & 127) == 0) mbar_arrive(bars + B_LAG);
        if (pos == 8) {
          if (decltype(gemm1)::value) {
            const uint32_t sa = sb + OFF_STAT + stat_off(tid_now());
            rha = 0.5f * __uint_as_float(lds32(sa + 4));
            rhb = 0.5f * __uint_as_float(lds32(sa + 68));
          } else {
            rha = __uint_as_float(ep & 1u);
          }
        }
        if (pos < 8) mbar_wait(bars + B_FULL + 8 * (pos + 1), ph);
        if (pos > 0) {
          wg_wait<1>();
          if (rel) mbar_arrive_cl(ebar + 8 * (pos - 1));
        }
      }
      wg_wait<0>();
      pin(acc);
      if (rel) mbar_arrive_cl(ebar + 64);
      ph ^= 1;
    };
    auto put_partials = [&](float (&acc)[64], const int pp) {
      const uint32_t par = __float_as_uint(rha);
#pragma unroll
      for (int hb = 0; hb < 2; hb++) {
        const bool b8 = pp == 0 && hb == 0;
        const uint32_t tn = tid_now();
        uint4* dst = b8 ? g_part + (size_t)((mt * 9 + 8) * 8 + 4 * w + warp) * 1024 + sl * 128 + (tn & 31)
                        : g_part + ((size_t)((mt * 9 + ((sl + 2 * pp + hb) & 7)) * 8 + sl) * 2 + w) * 512 + (tn & 127);
#pragma unroll
        for (int q = 0; q < 4; q++) {
          const float* s = &acc[32 * hb + 8 * q];
          stg128_rlx(dst + q * (b8 ? 32 : 128), (pack2(s[0], s[1]) & ~1u) | par, pack2(s[2], s[3]), pack2(s[4], s[5]), pack2(s[6], s[7]));
        }
      }
      if (pp < 2 && (tid_now() & 127) == 0) {
        sts32(bars + B_EPOCH + 4 + 4 * pp, clock());
        mbar_arrive(bars + B_PASS + 8 * pp);
      }
    };
    TR(3);
#pragma unroll 1
    for (int pass = 0; pass < 9; pass++) {
      {
        float acc[64];
        tile128(acc, make_desc(sb + OFF_XS + w * 8192, 16, 1024, 1), pass == 0, BoolC<false>(), BoolC<true>());
        TR(4 + 3 * pass);
        const uint32_t tn = tid_now();
        uint4* const park = g_hpark + (size_t)bid * (7 * 4 * 256) + (tn - 256);
        uint32_t hp[16];
#pragma unroll
        for (int i = 0; i < 16; i++) {
          const float rh = (i & 1) ? rhb : rha;
          const float g0 = acc[2 * i] * rh, g1 = acc[2 * i + 1] * rh;
          hp[i] = pack2(fmaf(g0, tanh_ap(g0), g0) * acc[32 + 2 * i], fmaf(g1, tanh_ap(g1), g1) * acc[33 + 2 * i]);
        }
        if (pass < 7) {
          if (pass == 5) fence_async_global();
#pragma unroll
          for (int q = 0; q < 4; q++) park[(pass * 4 + q) * 256] = make_uint4(hp[4 * q], hp[4 * q + 1], hp[4 * q + 2], hp[4 * q + 3]);
        } else {
          mbar_wait(bars + B_FREE, 0);
#pragma unroll
          for (int q = 0; q < 4; q++)
            stsm4(sb + OFF_HS - (pass - 7) * 16384 + (frag_off(tn) ^ (q << 5)), hp[4 * q], hp[4 * q + 1], hp[4 * q + 2], hp[4 * q + 3]);
          fence_async_smem();
          if (pass == 8) bar_sync(6 + w, 128);
        }
      }
      TR(5 + 3 * pass);
      if ((JOBMASK >> pass) & 1) {
        if (lead) {
          const int t = __popc(JOBMASK & ((1 << pass) - 1));
          mbar_wait(bars + B_CREADY + 8 * t, 0);
          conv_mma(sb + OFF_W, warp, tid_now() & 31, 6 + w);
          mbar_arrive(bars + B_CDONE + 8 * t);
          TR(6 + 3 * pass);
        }
        lead = !lead;
      }
    }
    const uint64_t dH = make_desc(sb + OFF_XS + 16384 + w * 8192, 16, 1024, 1);
    {
      float acc[64];
      tile128(acc, dH, false, BoolC<true>(), BoolC<false>());
      TR(4 + 27);
      put_partials(acc, 0);
      TR(5 + 27);
    }
#pragma unroll 1
    for (int pp = 1; pp < 4; pp++) {
      float acc[64];
      tile128(acc, dH, false, BoolC<false>(), BoolC<false>());
      TR(4 + 27 + 3 * pp);
      put_partials(acc, pp);
      TR(5 + 27 + 3 * pp);
    }
    {
      float acc[32];
      uint4 v[8];
      if (!lead) mbar_wait(bars + B_LAG, lagp);
#pragma unroll
      for (int pos = 0; pos < 9; pos++) {
        if (!(pos & 1)) mbar_wait(bars + B_FULL + 4 * pos, ph);
        const uint64_t d = dB + (uint64_t)(pos * 512);
        wg_fence();
#pragma unroll
        for (int kk = 0; kk < 4; kk++) {
          if (pos <= 1) mma_n64_ss(acc, dH + (uint64_t)(pos * 1024 + kk * 2), d + kk * 128, (pos | kk) != 0);
          else {
            const int o = 16 * (pos - 2) + 4 * kk;
            mma_n64_rs(acc, a[o], a[o + 1], a[o + 2], a[o + 3], d + kk * 128, 1);
          }
        }
        if (pos == 1 && lead && (tid_now() & 127) == 0) mbar_arrive(bars + B_LAG);
      }
      wg_commit();
      TR(50);
      const uint32_t tn = tid_now();
      const int tid = tn & 127, lane = tn & 31;
      const uint4* inbox = g_part + ((size_t)((mt * 9 + sl) * 8) * 2 + w) * 512 + tid;
#pragma unroll
      for (int k = 0; k < 8; k++) v[k] = ldg128_cg(inbox + ((sl - 4 - (k >> 2)) & 7) * 1024 + (k & 3) * 128);
      const uint32_t par = ep & 1u;
      const float ra = __uint_as_float(lds32(sb + OFF_STAT + stat_off(tn) + 4)), rb = __uint_as_float(lds32(sb + OFF_STAT + stat_off(tn) + 68));
      float pre[32];
      wg_wait<0>();
      pin(acc);
      uint4 z[8];
#pragma unroll
      for (int k = 0; k < 8; k++) z[k] = ldg128_cg(inbox + ((sl + 1 + (k >> 2)) & 7) * 1024 + (k & 3) * 128);

      mbar_wait(bars + B_PRESUM, 0);
#pragma unroll 1
      for (int it = 0; it < 4000; it++) {
        uint32_t m = 0;
#pragma unroll
        for (int k = 0; k < 8; k++) m |= v[k].x ^ par;
        if (!__any_sync(0xffffffffu, m & 1u)) break;
#pragma unroll
        for (int k = 0; k < 8; k++) v[k] = ldg128_cg(inbox + ((sl - 4 - (k >> 2)) & 7) * 1024 + (k & 3) * 128);
      }
      TR(51);
#pragma unroll
      for (int q = 0; q < 4; q++) {
        uint32_t b[4], t[4];
        lds128(b[0], b[1], b[2], b[3], sb + OFF_XS + w * 8192 + warp * 2048 + q * 512 + lane * 16);
        lds128(t[0], t[1], t[2], t[3], sb + OFF_B1 + w * 8192 + q * 2048 + tid * 16);
        const uint32_t e[4] = {v[q].x, v[q].y, v[q].z, v[q].w}, f[4] = {v[4 + q].x, v[4 + q].y, v[4 + q].z, v[4 + q].w};
#pragma unroll
        for (int i = 0; i < 4; i++) {
          const float r = (i & 1) ? rb : ra;
          const uint32_t ef = hadd2(e[i], f[i]);
          pre[8 * q + 2 * i] = fmaf(r, acc[8 * q + 2 * i] + (bf_lo(ef) + bf_lo(t[i])), bf_lo(b[i]));
          pre[8 * q + 2 * i + 1] = fmaf(r, acc[8 * q + 2 * i + 1] + (bf_hi(ef) + bf_hi(t[i])), bf_hi(b[i]));
        }
      }
#pragma unroll 1
      for (int it = 0; it < 4000; it++) {
        uint32_t m = 0;
#pragma unroll
        for (int k = 0; k < 8; k++) m |= z[k].x ^ par;
        if (!__any_sync(0xffffffffu, m & 1u)) break;
#pragma unroll 1
        for (int i2 = 0; i2 < 4000; i2++)
          if (!__any_sync(0xffffffffu, (ldg32_cg(inbox + ((sl + 1 + (lane & 1)) & 7) * 1024 + 384) ^ par) & 1u)) break;
#pragma unroll
        for (int k = 0; k < 8; k++) z[k] = ldg128_cg(inbox + ((sl + 1 + (k >> 2)) & 7) * 1024 + (k & 3) * 128);
      }
      TR(52);
      uint32_t ow[16];
#pragma unroll
      for (int q = 0; q < 4; q++) {
        const uint32_t pa[4] = {z[q].x, z[q].y, z[q].z, z[q].w}, pb[4] = {z[4 + q].x, z[4 + q].y, z[4 + q].z, z[4 + q].w};
#pragma unroll
        for (int i = 0; i < 4; i++) {
          const float r = (i & 1) ? rb : ra;
          const uint32_t ab = hadd2(pa[i], pb[i]);
          ow[4 * q + i] = pack2(fmaf(r, bf_lo(ab), pre[8 * q + 2 * i]), fmaf(r, bf_hi(ab), pre[8 * q + 2 * i + 1]));
        }
      }
#pragma unroll
      for (int q = 0; q < 4; q++) stsm4(sb + OFF_HS + (frag_off(tn) ^ (q << 5)), ow[4 * q], ow[4 * q + 1], ow[4 * q + 2], ow[4 * q + 3]);
      __syncwarp();
#pragma unroll
      for (int q = 0; q < 4; q++) {
        const uint32_t row = w * 64 + warp * 16 + q * 4 + (lane >> 3);
        uint32_t o0, o1, o2, o3;
        lds128(o0, o1, o2, o3, sb + OFF_HS + row * 128 + (((lane & 7) ^ (row & 7)) << 4));
        stg128(p.out + (size_t)(mt * 128 + row) * D_ + sl * 64 + (lane & 7) * 8, o0, o1, o2, o3);
      }
      TR(53);
    }
  }
}

#undef ep

#define PROMO CU_TENSOR_MAP_L2_PROMOTION_L2_128B
typedef CUresult (*EncodeFn)(CUtensorMap*, CUtensorMapDataType, cuuint32_t, void*, const cuuint64_t*, const cuuint64_t*, const cuuint32_t*,
                             const cuuint32_t*, CUtensorMapInterleave, CUtensorMapSwizzle, CUtensorMapL2promotion, CUtensorMapFloatOOBfill);

void make_map(EncodeFn enc, CUtensorMap* m, const void* ptr, uint64_t inner, uint64_t outer, uint32_t box_outer) {
  cuuint64_t gd[2] = {inner, outer};
  cuuint64_t gs[1] = {inner * 2};
  cuuint32_t bd[2] = {64, box_outer};
  cuuint32_t es[2] = {1, 1};
  enc(m, CU_TENSOR_MAP_DATA_TYPE_BFLOAT16, 2, const_cast<void*>(ptr), gd, gs, bd, es, CU_TENSOR_MAP_INTERLEAVE_NONE, CU_TENSOR_MAP_SWIZZLE_128B,
      PROMO, CU_TENSOR_MAP_FLOAT_OOB_FILL_NONE);
}

}

extern "C" void kernel_launch(void* const* d_in, const int* in_sizes, int n_in, void* d_out, int out_size) {
  (void)in_sizes; (void)n_in; (void)out_size;
  static EncodeFn enc = nullptr;
  if (!enc) {
    void* fn = nullptr;
    cudaDriverEntryPointQueryResult q;
    cudaGetDriverEntryPoint("cuTensorMapEncodeTiled", &fn, cudaEnableDefault, &q);
    enc = (EncodeFn)fn;
    cudaFuncSetAttribute(fused_kernel, cudaFuncAttributeMaxDynamicSharedMemorySize, SMEM_BYTES);
  }
  CUtensorMap m1, m3, m2, mx;
  make_map(enc, &m1, d_in[10], F_, D_, 64);
  make_map(enc, &m3, d_in[11], F_, D_, 64);
  make_map(enc, &m2, d_in[12], D_, F_, 64);
  make_map(enc, &mx, d_in[0], D_, L_, 128);
  Params p;
  p.x = (const __nv_bfloat16*)d_in[0];
  p.a_re = (const __nv_bfloat16*)d_in[1];
  p.a_im = (const __nv_bfloat16*)d_in[2];
  p.b_re = (const __nv_bfloat16*)d_in[3];
  p.b_im = (const __nv_bfloat16*)d_in[4];
  p.c_re = (const __nv_bfloat16*)d_in[5];
  p.c_im = (const __nv_bfloat16*)d_in[6];
  p.log_dt = (const __nv_bfloat16*)d_in[7];
  p.dskip = (const __nv_bfloat16*)d_in[8];
  p.out = (__nv_bfloat16*)d_out;
  cudaLaunchConfig_t cfg = {};
  cfg.gridDim = dim3(132);
  cfg.blockDim = dim3(512);
  cfg.dynamicSmemBytes = SMEM_BYTES;
  cfg.stream = cudaStreamPerThread;
  cudaLaunchAttribute at[1];
  at[0].id = cudaLaunchAttributeClusterDimension;
  at[0].val.clusterDim.x = 2;
  at[0].val.clusterDim.y = 1;
  at[0].val.clusterDim.z = 1;
  cfg.attrs = at;
  cfg.numAttrs = 1;
  cudaLaunchKernelEx(&cfg, fused_kernel, m1, m3, m2, mx, p);
}
```
